```python
import torch

def _softmax(x, axis=-1):
    return torch.softmax(x, dim=axis)
def _gelu(x):
    return torch.nn.functional.gelu(x, approximate="tanh")
def _silu(x):
    return torch.nn.functional.silu(x)
def _sigmoid(x):
    return torch.sigmoid(x)
def _layernorm(x, axis=-1, eps=1e-5):
    m = x.mean(dim=axis, keepdim=True)
    v = x.var(dim=axis, keepdim=True, unbiased=False)
    return (x - m) / torch.sqrt(v + eps)
def _scatter_add(tgt, idx, src, axis=0):
    return tgt.clone().index_add_(axis, idx, src)
def _segment_sum(src, seg, n):
    out = torch.zeros((n,) + src.shape[1:], dtype=src.dtype)
    return out.index_add_(0, seg, src)
def _pad(x, pw):
    flat = tuple(v for pair in reversed(pw) for v in pair)
    return torch.nn.functional.pad(x, flat)

kernel_name = 'interleave_layers__gqa_block_cached__dense_activation_gelu__decode'

def setup_inputs():

    _w = (lambda a: (lambda t: t.to(torch.bfloat16) if t.is_floating_point() else t)(torch.as_tensor(a)))
    def _A_setup():
        B, Sq, D = 1, 1, 448
        Hq, Hkv, Sk, Dh = 16, 8, 65536, 256
        assert Hq % Hkv == 0, (Hq, Hkv)
        return {
            "x": _w((lambda *s: torch.randn(*s, dtype=torch.bfloat16) * 0.05)(B, Sq, D)),
            "k_cache": _w((lambda *s: torch.randn(*s, dtype=torch.bfloat16) * 0.8)(B, Hkv, Sk, Dh)),
            "v_cache": _w((lambda *s: torch.randn(*s, dtype=torch.bfloat16) * 1.6)(B, Hkv, Sk, Dh)),
            "wq": _w((lambda *s: torch.randn(*s, dtype=torch.bfloat16) * 0.8)(D, Hq * Dh) * (D ** -0.5)),
            "wo": _w((lambda *s: torch.randn(*s, dtype=torch.bfloat16) * 1.6)(Hq * Dh, D) * ((Hq * Dh) ** -0.5)),
        }
    _A_in = _A_setup()

    def _B_setup():
        B, S, D, F = 1, 1, 448, 1792
        return {
            "x": _w((lambda *s: torch.randn(*s, dtype=torch.bfloat16) * 0.05)(B, S, D)),
            "w1": _w((lambda *s: torch.randn(*s, dtype=torch.bfloat16) * 0.2)(D, F) * (D ** -0.5)),
            "b1": _w((lambda *s: torch.randn(*s, dtype=torch.bfloat16) * 0.2)(F) * 0.01),
            "w2": _w((lambda *s: torch.randn(*s, dtype=torch.bfloat16) * 0.2)(F, D) * (F ** -0.5)),
            "b2": _w((lambda *s: torch.randn(*s, dtype=torch.bfloat16) * 0.2)(D) * 0.01),
        }
    _B_in = _B_setup()

    return {
        "A_x": _A_in["x"],
        "A_k_cache": _A_in["k_cache"],
        "A_v_cache": _A_in["v_cache"],
        "A_wq": _A_in["wq"],
        "A_wo": _A_in["wo"],
        "B_x": _B_in["x"],
        "B_w1": _B_in["w1"],
        "B_b1": _B_in["b1"],
        "B_w2": _B_in["w2"],
        "B_b2": _B_in["b2"],
    }

def reference(A_x, A_k_cache, A_v_cache, A_wq, A_wo, B_x, B_w1, B_b1, B_w2, B_b2):
    def _A_ref(x, k_cache, v_cache, wq, wo):
        B, Sq, D = x.shape
        Hq, Dh = 16, 256
        Hkv = k_cache.shape[1]
        rep = Hq // Hkv
        q = (lambda x, *d: x.permute(*d))((x @ wq).reshape(B, Sq, Hq, Dh), 0, 2, 1, 3)
        k = (lambda x, n, axis: torch.repeat_interleave(x, n, dim=axis))(k_cache, rep, axis=1)
        v = (lambda x, n, axis: torch.repeat_interleave(x, n, dim=axis))(v_cache, rep, axis=1)
        scores = torch.einsum("bhqd,bhkd->bhqk", q, k) * (Dh ** -0.5)
        p = _softmax(scores, axis=-1)
        o = torch.einsum("bhqk,bhkd->bhqd", p, v)
        return (lambda x, *d: x.permute(*d))(o, 0, 2, 1, 3).reshape(B, Sq, Hq * Dh) @ wo

    def _B_ref(x, w1, b1, w2, b2):
        h = torch.einsum("bsd,df->bsf", x, w1) + b1
        h = _gelu(h)
        return torch.einsum("bsf,fd->bsd", h, w2) + b2

    x = A_x
    x = x + _A_ref(_layernorm(x, axis=-1), A_k_cache, A_v_cache, A_wq, A_wo)
    x = x + _B_ref(_layernorm(x, axis=-1), B_w1, B_b1, B_w2, B_b2)
    x = x + _A_ref(_layernorm(x, axis=-1), A_k_cache, A_v_cache, A_wq, A_wo)
    x = x + _B_ref(_layernorm(x, axis=-1), B_w1, B_b1, B_w2, B_b2)
    return x
```

```cpp
#include <cuda_runtime.h>
#include <cuda_bf16.h>
#include <cuda.h>
#include <stdint.h>

namespace {

constexpr int DM = 448;
constexpr int FF = 1792;
constexpr int NQ = 4096;
constexpr int TPH = 2048;
constexpr int NT = 8 * TPH;
constexpr int OWN0 = 7 * TPH;
#define NS_ 7
#define NA_ 6
#define DEPTH_MAIN_ 2
#define INITF_ 2
#define NSTAT2_ 3
#define REREAD 2
#define JCNT 5
#define PIECE_ 4096
constexpr int NS = NS_;
constexpr int NA = NA_;
constexpr int DEPTH_MAIN = DEPTH_MAIN_;
constexpr int INITF = INITF_;
constexpr int PIECE = PIECE_;
constexpr int NSTAT2 = NSTAT2_;
constexpr int REG_H = NA * 32 + 8;
constexpr int REG_C = (488 - 2 * REG_H) < 120 ? (488 - 2 * REG_H) : 120;
constexpr int SLOT = 32768;
constexpr int MAXG = 256;
constexpr int OWNCAP = 32;
constexpr int SPIN_MAX = 1 << 22;

constexpr int M_USE1 = 1 << 8;
constexpr int M_SVC = 1 << 9;
constexpr int M_SIDE = 1 << 10;
constexpr int M_END = 1 << 11;
constexpr int M_NOP = 1 << 12;

constexpr int OFF_SC = NS * SLOT;
constexpr int OFF_RED = OFF_SC + 2048;
constexpr int OFF_FULL = OFF_RED + 512;
constexpr int OFF_EMPTY = OFF_FULL + 64;
constexpr int OFF_HREQ = OFF_EMPTY + 64;
constexpr int OFF_META = OFF_HREQ + 64;
constexpr int OFF_HSLOT = OFF_META + 32;
constexpr int OFF_JB = OFF_HSLOT + 32;
constexpr int OFF_XO = OFF_JB + 32;
constexpr int OFF_OWN = OFF_XO + 128;
constexpr int SMEM_TOTAL = OFF_OWN + OWNCAP * 2;
static_assert(SMEM_TOTAL <= 232448, "smem");
static_assert(NS <= 8 && NA <= 8, "bars");

__device__ uint4 g_rec[3 * 128 * MAXG * 2];
__device__ uint4 g_q[1024];
__device__ uint4 g_ma[14 * 128 * 8];
__device__ uint4 g_mb[128 * 112];
__device__ __align__(128) unsigned g_ctr0[32];
__device__ __align__(128) unsigned g_ctr1[32];
__device__ unsigned g_epoch;
#define TS(i)

__device__ __forceinline__ uint32_t smem_u32(const void* p) { return (uint32_t)__cvta_generic_to_shared(p); }
__device__ __forceinline__ int tid_now() {
    int t;
    asm volatile("mov.u32 %0, %tid.x;" : "=r"(t));
    return t;
}
__device__ __forceinline__ uint64_t pol_first() {
    uint64_t p;
    asm volatile("createpolicy.fractional.L2::evict_first.b64 %0, 1.0;" : "=l"(p));
    return p;
}
__device__ __forceinline__ uint64_t pol_normal() {
    uint64_t p;
    asm volatile("createpolicy.fractional.L2::evict_normal.b64 %0, 1.0;" : "=l"(p));
    return p;
}
__device__ __forceinline__ uint64_t pol_reread() {
    uint64_t p;
    asm volatile("createpolicy.fractional.L2::evict_unchanged.b64 %0, 1.0;" : "=l"(p));
    return p;
}
__device__ __forceinline__ void mbar_init(uint32_t bar, int cnt) {
    asm volatile("mbarrier.init.shared.b64 [%0], %1;" ::"r"(bar), "r"(cnt) : "memory");
}
__device__ __forceinline__ void mbar_expect(uint32_t bar, uint32_t bytes) {
    asm volatile("mbarrier.arrive.expect_tx.shared.b64 _, [%0], %1;" ::"r"(bar), "r"(bytes) : "memory");
}
__device__ __forceinline__ void mbar_arrive(uint32_t bar) {
    asm volatile("mbarrier.arrive.shared.b64 _, [%0];" ::"r"(bar) : "memory");
}
__device__ __forceinline__ void mbar_wait(uint32_t bar, uint32_t parity) {
    int it = 0;
    while (true) {
        uint32_t ok;
        asm volatile("{\n.reg .pred p;\nmbarrier.try_wait.parity.shared.b64 p, [%1], %2;\nselp.u32 %0, 1, 0, p;\n}"
                     : "=r"(ok) : "r"(bar), "r"(parity) : "memory");
        if (ok) break;
        if (++it > SPIN_MAX) __trap();
    }
}
__device__ __forceinline__ void tma4(uint32_t dst, const CUtensorMap* tm, int c3, uint32_t bar, uint64_t pol) {
    asm volatile(
        "cp.async.bulk.tensor.4d.shared::cluster.global.mbarrier::complete_tx::bytes.L2::cache_hint "
        "[%0], [%1, {%3,%3,%3,%4}], [%2], %5;" ::"r"(dst), "l"(tm), "r"(bar), "r"(0), "r"(c3), "l"(pol) : "memory");
}
__device__ __forceinline__ void tma4_prefetch(const CUtensorMap* tm, int c3, uint64_t pol) {
    asm volatile("cp.async.bulk.prefetch.tensor.4d.L2.global.L2::cache_hint [%0, {%1,%1,%1,%2}], %3;" ::"l"(tm), "r"(0), "r"(c3), "l"(pol) : "memory");
}
__device__ __forceinline__ unsigned ticket(int which) {
    unsigned r;
    if (which) asm volatile("atom.relaxed.gpu.global.add.u32 %0, [%1], 1;" : "=r"(r) : "l"(g_ctr1) : "memory");
    else asm volatile("atom.relaxed.gpu.global.add.u32 %0, [%1], 1;" : "=r"(r) : "l"(g_ctr0) : "memory");
    return r;
}
__device__ __forceinline__ void l2_prefetch(const void* src, uint32_t bytes) {
    asm volatile("cp.async.bulk.prefetch.L2.global [%0], %1;" ::"l"(src), "r"(bytes) : "memory");
}
__device__ __forceinline__ void bar_c() { asm volatile("bar.sync 1, 128;" ::: "memory"); }
__device__ __forceinline__ bool bar_c_and(bool v) {
    uint32_t r;
    asm volatile("{\n.reg .pred p, q;\nsetp.ne.u32 q, %1, 0;\nbar.red.and.pred p, 3, 128, q;\nselp.u32 %0, 1, 0, p;\n}"
                 : "=r"(r) : "r"((uint32_t)v) : "memory");
    return r != 0;
}
__device__ __forceinline__ void ldsm4(uint32_t* r, uint32_t a) {
    asm volatile("ldmatrix.sync.aligned.m8n8.x4.shared.b16 {%0,%1,%2,%3}, [%4];"
                 : "=r"(r[0]), "=r"(r[1]), "=r"(r[2]), "=r"(r[3]) : "r"(a) : "memory");
}
__device__ __forceinline__ void ldsm4t(uint32_t* r, uint32_t a) {
    asm volatile("ldmatrix.sync.aligned.m8n8.x4.trans.shared.b16 {%0,%1,%2,%3}, [%4];"
                 : "=r"(r[0]), "=r"(r[1]), "=r"(r[2]), "=r"(r[3]) : "r"(a) : "memory");
}
__device__ __forceinline__ void mma16816(float* c, const uint32_t* a, uint32_t b0, uint32_t b1) {
    asm volatile("mma.sync.aligned.m16n8k16.row.col.f32.bf16.bf16.f32 {%0,%1,%2,%3}, {%4,%5,%6,%7}, {%8,%9}, {%0,%1,%2,%3};"
                 : "+f"(c[0]), "+f"(c[1]), "+f"(c[2]), "+f"(c[3])
                 : "r"(a[0]), "r"(a[1]), "r"(a[2]), "r"(a[3]), "r"(b0), "r"(b1));
}
__device__ __forceinline__ void st_pkt(void* p, uint32_t a, uint32_t b, uint32_t c, uint32_t d) {
    asm volatile("{\n.reg .b128 v;\n.reg .b64 lo, hi;\nmov.b64 lo, {%1,%2};\nmov.b64 hi, {%3,%4};\nmov.b128 v, {lo,hi};\n"
                 "st.relaxed.gpu.global.b128 [%0], v;\n}" ::"l"(p), "r"(a), "r"(b), "r"(c), "r"(d) : "memory");
}
__device__ __forceinline__ uint4 ld_pkt(const void* p) {
    uint4 r;
    asm volatile("{\n.reg .b128 v;\n.reg .b64 lo, hi;\nld.relaxed.gpu.global.b128 v, [%4];\nmov.b128 {lo,hi}, v;\n"
                 "mov.b64 {%0,%1}, lo;\nmov.b64 {%2,%3}, hi;\n}"
                 : "=r"(r.x), "=r"(r.y), "=r"(r.z), "=r"(r.w) : "l"(p) : "memory");
    return r;
}
__device__ __forceinline__ void st_pkt4(void* p, const float* v, uint32_t tag) {
    st_pkt(p, __byte_perm(__float_as_uint(v[0]), tag, 0x3214), __byte_perm(__float_as_uint(v[1]), tag, 0x3215),
           __byte_perm(__float_as_uint(v[2]), tag, 0x3216), __byte_perm(__float_as_uint(v[3]), tag, 0x3217));
}
__device__ __forceinline__ uint32_t pkt4_tag(const uint4& a) {
    return __byte_perm(__byte_perm(a.x, a.y, 0x0040), __byte_perm(a.z, a.w, 0x0040), 0x5410);
}
__device__ __forceinline__ uint4 ldg128(const void* p, uint64_t pol) {
    uint4 r;
    asm volatile("ld.global.nc.L1::no_allocate.L2::cache_hint.v4.u32 {%0,%1,%2,%3}, [%4], %5;"
                 : "=r"(r.x), "=r"(r.y), "=r"(r.z), "=r"(r.w) : "l"(p), "l"(pol) : "memory");
    return r;
}
__device__ __forceinline__ uint2 ldg64p(const void* p, uint64_t pol) {
    uint2 r;
    asm volatile("ld.global.nc.L1::no_allocate.L2::cache_hint.v2.u32 {%0,%1}, [%2], %3;" : "=r"(r.x), "=r"(r.y) : "l"(p), "l"(pol) : "memory");
    return r;
}
__device__ __forceinline__ uint2 ldg64(const void* p) {
    uint2 r;
    asm volatile("ld.global.nc.L1::no_allocate.v2.u32 {%0,%1}, [%2];" : "=r"(r.x), "=r"(r.y) : "l"(p) : "memory");
    return r;
}
__device__ __forceinline__ float bf_lo(uint32_t u) { return __uint_as_float(u << 16); }
__device__ __forceinline__ float bf_hi(uint32_t u) { return __uint_as_float(u & 0xffff0000u); }
__device__ __forceinline__ uint32_t pack_bf(float lo, float hi) {
    uint32_t r;
    asm("cvt.rn.bf16x2.f32 %0, %1, %2;" : "=r"(r) : "f"(hi), "f"(lo));
    return r;
}
__device__ __forceinline__ float warp_max(float x) {
    int k = __float_as_int(x);
    k ^= (k >> 31) & 0x7fffffff;
    k = __reduce_max_sync(0xffffffffu, k);
    k ^= (k >> 31) & 0x7fffffff;
    return __int_as_float(k);
}
__device__ __forceinline__ float bfr(float x) { return __uint_as_float(pack_bf(0.f, x)); }
__device__ __forceinline__ float ex2(float x) {
    float r;
    asm("ex2.approx.ftz.f32 %0, %1;" : "=f"(r) : "f"(x));
    return r;
}

struct St {
    float acc[16];
    uint32_t q[8];
    float m0, l0, m1, l1;
};

struct Params {
    const __nv_bfloat16 *x, *k, *v, *wq, *wo, *w1, *b1, *w2, *b2;
    __nv_bfloat16* out;
    int ta0, tkeep;
};

__device__ __forceinline__ void st_loadq(St& s, int h0, int h1, uint32_t tag) {
    const int tid = tid_now();
    const int lane = tid & 31, w = tid >> 5;
    const int h = lane < 16 ? h0 : h1;
    const uint4* p = g_q + (((2 * h + ((lane >> 2) & 1)) * 4 + w) * 16 + (lane & 3));
    int it = 0;
    while (true) {
        uint4 a = ld_pkt(p), b = ld_pkt(p + 4), c = ld_pkt(p + 8), d = ld_pkt(p + 12);
        s.q[0] = a.x; s.q[1] = a.y; s.q[2] = b.x; s.q[3] = b.y;
        s.q[4] = c.x; s.q[5] = c.y; s.q[6] = d.x; s.q[7] = d.y;
        if (__all_sync(0xffffffffu, a.z == tag && b.z == tag && c.z == tag && d.z == tag)) break;
        if (++it > SPIN_MAX) __trap();
    }
}

__device__ __forceinline__ void st_flush(St& s, int sg, int buf, int G, int cta, uint32_t tag) {
    const int tid = tid_now();
    float l = sg ? s.l1 : s.l0;
    l += __shfl_xor_sync(0xffffffffu, l, 1);
    l += __shfl_xor_sync(0xffffffffu, l, 2);
    l += __shfl_xor_sync(0xffffffffu, l, 4);
    l += __shfl_xor_sync(0xffffffffu, l, 8);
    const int u = tid & 1;
    const float y = u ? l : (sg ? s.m1 : s.m0);
    float ml[2];
    ml[0] = __shfl_sync(0xffffffffu, y, u);
    ml[1] = __shfl_sync(0xffffffffu, y, 16 + u);
    if (((tid >> 1) & 1) == sg) {
        uint4* p = g_rec + ((size_t)(buf * 128 + (tid & ~3)) * G + cta) * 2 + u;
#pragma unroll
        for (int r = 0; r < 4; r++) {
            const int o = (r & 1) * 2 + (r >> 1);
            st_pkt(p, __float_as_uint(u ? s.acc[8 + o] : s.acc[o]), __float_as_uint(u ? s.acc[12 + o] : s.acc[4 + o]),
                   __float_as_uint(ml[r >> 1]), tag);
            p += G * 2;
        }
#pragma unroll
        for (int i = 0; i < 16; i++) s.acc[i] = 0.f;
    }
    if (sg) { s.m1 = -INFINITY; s.l1 = 0.f; }
    else { s.m0 = -INFINITY; s.l0 = 0.f; }
    __syncwarp();
}

__device__ __forceinline__ bool combine(bool block, float* xacc, int h, int buf, int G, int cta, uint32_t tag,
                                        const __nv_bfloat16* wo, float* red) {
    const int tid = tid_now();
    const int j = cta & 127;
    const uint4* p = g_rec + ((size_t)(buf * 128 + j) * G + tid) * 2;
    const bool two = tid + 128 < G;
    const uint4* p2 = two ? p + 256 : p;
    uint2 wr[4];
    {
        const int row0 = (2 * h + ((j >> 1) & 1)) * 256 + (j >> 5) * 64 + ((j >> 2) & 7) + (j & 1) * 8;
        const __nv_bfloat16* wp = wo + (size_t)row0 * DM + (tid < 112 ? tid : 0) * 4;
        const uint64_t pol = pol_first();
#pragma unroll
        for (int i = 0; i < 4; i++) wr[i] = ldg64p(wp + i * 16 * DM, pol);
    }
    float s[5], m1;
    TS((tag & 16) ? 26 : 19);
    {
        uint4 a, b, c, d;
        int it = 0;
        bool ok;
        while (true) {
            a = ld_pkt(p);
            b = ld_pkt(p + 1);
            c = ld_pkt(p2);
            d = ld_pkt(p2 + 1);
            ok = __all_sync(0xffffffffu, a.w == tag && b.w == tag && c.w == tag && d.w == tag);
            if (ok || !block) break;
            if (++it > SPIN_MAX) __trap();
        }
        if (!block) {
            if (!bar_c_and(ok)) return false;
        }
        TS((tag & 16) ? 27 : 20);
        const float ma = __uint_as_float(a.z), mb = two ? __uint_as_float(c.z) : -INFINITY;
        m1 = warp_max(fmaxf(ma, mb));
        const float ms = (m1 == -INFINITY) ? 0.f : m1;
        const float f1 = ex2(ma - ms), f2 = ex2(mb - ms);
        s[0] = f1 * __uint_as_float(a.x) + f2 * __uint_as_float(c.x);
        s[1] = f1 * __uint_as_float(a.y) + f2 * __uint_as_float(c.y);
        s[2] = f1 * __uint_as_float(b.x) + f2 * __uint_as_float(d.x);
        s[3] = f1 * __uint_as_float(b.y) + f2 * __uint_as_float(d.y);
        s[4] = f1 * __uint_as_float(b.z) + f2 * __uint_as_float(d.z);
    }
#pragma unroll
    for (int o = 16; o > 0; o >>= 1) {
#pragma unroll
        for (int i = 0; i < 5; i++) s[i] += __shfl_xor_sync(0xffffffffu, s[i], o);
    }
    if ((tid & 31) == 0) {
        *(float4*)(red + (tid >> 5) * 8) = make_float4(s[0], s[1], s[2], s[3]);
        *(float2*)(red + (tid >> 5) * 8 + 4) = make_float2(s[4], m1);
    }
    bar_c();
    TS((tag & 16) ? 28 : 11);
    float M = -INFINITY;
#pragma unroll
    for (int i = 0; i < 4; i++) M = fmaxf(M, red[i * 8 + 5]);
    float o4[4] = {0.f, 0.f, 0.f, 0.f}, L = 0.f;
#pragma unroll
    for (int i = 0; i < 4; i++) {
        float4 v = *(const float4*)(red + i * 8);
        float2 lm = *(const float2*)(red + i * 8 + 4);
        float f = ex2(lm.y - M);
        o4[0] += f * v.x; o4[1] += f * v.y; o4[2] += f * v.z; o4[3] += f * v.w;
        L += f * lm.x;
    }
    const float inv = __fdividef(1.f, L);
#pragma unroll
    for (int i = 0; i < 4; i++) {
        float o = bfr(o4[i] * inv);
        xacc[0] += o * bf_lo(wr[i].x);
        xacc[1] += o * bf_hi(wr[i].x);
        xacc[2] += o * bf_lo(wr[i].y);
        xacc[3] += o * bf_hi(wr[i].y);
    }
    return true;
}

__device__ __forceinline__ void ln_stats(uint2 xp, float* xs, int tid, float& mean, float& sd) {
    if (tid < 112) *(float4*)(xs + tid * 4) = make_float4(bf_lo(xp.x), bf_hi(xp.x), bf_lo(xp.y), bf_hi(xp.y));
    bar_c();
    const int lane = tid & 31;
    const float c = xs[0];
    float s = 0.f, q = 0.f;
#pragma unroll
    for (int i = 0; i < 14; i++) {
        float d = xs[lane + 32 * i] - c;
        s += d;
        q += d * d;
    }
#pragma unroll
    for (int o = 16; o > 0; o >>= 1) {
        s += __shfl_xor_sync(0xffffffffu, s, o);
        q += __shfl_xor_sync(0xffffffffu, q, o);
    }
    const float ms = s * (1.f / DM);
    float var = fmaxf(q * (1.f / DM) - ms * ms, 0.f);
    mean = bfr(c + ms);
    sd = bfr(sqrtf(bfr(bfr(var) + 1e-5f)));
}
__device__ __forceinline__ float ln_apply(float x, float mean, float sd) { return bfr(__fdividef(bfr(x - mean), sd)); }

__device__ __forceinline__ void fma8(float* s, float z, const uint4& u) {
    s[0] += z * bf_lo(u.x); s[1] += z * bf_hi(u.x);
    s[2] += z * bf_lo(u.y); s[3] += z * bf_hi(u.y);
    s[4] += z * bf_lo(u.z); s[5] += z * bf_hi(u.z);
    s[6] += z * bf_lo(u.w); s[7] += z * bf_hi(u.w);
}

__device__ __forceinline__ void load_wq(uint4* wr, const __nv_bfloat16* wq, int cta, int tid) {
    const __nv_bfloat16* p = wq + (size_t)(tid >> 2) * NQ + ((cta + 64) & 127) * 32 + (tid & 3) * 8;
    const uint64_t pol = pol_first();
#pragma unroll
    for (int r = 0; r < 14; r++) wr[r] = ldg128(p + (size_t)r * 32 * NQ, pol);
}

__device__ __forceinline__ void q_phase(const uint4* wr, uint2 xv, float* xs, float* red, int cta, int tid, uint32_t tag) {
    float mean, sd;
    ln_stats(xv, xs, tid, mean, sd);
    TS((tag & 16) ? 21 : 29);
    float s[8];
#pragma unroll
    for (int i = 0; i < 8; i++) s[i] = 0.f;
#pragma unroll
    for (int r = 0; r < 14; r++) fma8(s, ln_apply(xs[(tid >> 2) + 32 * r], mean, sd), wr[r]);
    const int lane = tid & 31, w = tid >> 5;
    {
        const bool up = lane & 16;
#pragma unroll
        for (int i = 0; i < 4; i++) {
            float send = up ? s[i] : s[i + 4];
            float keep = up ? s[i + 4] : s[i];
            s[i] = keep + __shfl_xor_sync(0xffffffffu, send, 16);
        }
    }
    {
        const bool up = lane & 8;
#pragma unroll
        for (int i = 0; i < 2; i++) {
            float send = up ? s[i] : s[i + 2];
            float keep = up ? s[i + 2] : s[i];
            s[i] = keep + __shfl_xor_sync(0xffffffffu, send, 8);
        }
    }
    {
        const bool up = lane & 4;
        float send = up ? s[0] : s[1];
        float keep = up ? s[1] : s[0];
        s[0] = keep + __shfl_xor_sync(0xffffffffu, send, 4);
    }
    const int col = (lane & 3) * 8 + ((lane >> 4) & 1) * 4 + ((lane >> 3) & 1) * 2 + ((lane >> 2) & 1);
    red[w * 32 + col] = s[0];
    TS((tag & 16) ? 22 : 30);
    bar_c();
    if (tid < 8) {
        const int c0 = (tid >> 2) * 16 + (tid & 3) * 2;
        float v[4];
#pragma unroll
        for (int i = 0; i < 4; i++) {
            const int c = c0 + (i & 1) + (i >> 1) * 8;
            v[i] = (red[c] + red[32 + c]) + (red[64 + c] + red[96 + c]);
        }
        st_pkt(g_q + ((cta + 64) & 127) * 8 + tid, pack_bf(v[0], v[1]), pack_bf(v[2], v[3]), tag, tag);
    }
    bar_c();
}

__device__ __forceinline__ uint2 mb_poll(int cta, int tid, uint32_t tag) {
    const uint4* p = g_mb + cta * 112 + (tid < 112 ? tid : tid - 16);
    int it = 0;
    while (true) {
        const uint4 a = ld_pkt(p);
        if (__all_sync(0xffffffffu, a.z == tag)) return make_uint2(a.x, a.y);
        if (++it > SPIN_MAX) __trap();
    }
}

__device__ __forceinline__ float gelu_tanh(float x) {
    const float u = 0.7978845608028654f * (x + 0.044715f * x * x * x);
    return 0.5f * x * (1.f + tanhf(u));
}

__device__ __forceinline__ void tile_step(St& s, bool sg, uint32_t ka, uint32_t va, uint32_t scw, uint32_t scr, uint32_t lb,
                                          uint32_t ebar) {
    const float SC = 0.0625f * 1.4426950408889634f;
    float c[2][4];
#pragma unroll
    for (int mt = 0; mt < 2; mt++) c[mt][0] = c[mt][1] = c[mt][2] = c[mt][3] = 0.f;
    {
        uint32_t a[8][4];
#pragma unroll
        for (int i = 0; i < 8; i++) ldsm4(a[i], (ka ^ ((i >> 1) * 32)) + (i & 1) * 8192);
#pragma unroll
        for (int i = 0; i < 8; i++) mma16816(c[i & 1], a[i], s.q[i & 6], s.q[(i & 6) + 1]);
    }
    const bool mine = ((lb & 2) != 0) == sg;
    {
        const bool t1 = lb & 1;
        asm volatile("{\n.reg .pred p;\nsetp.ne.u32 p, %5, 0;\n@p st.shared.f32 [%0], %1;\n@p st.shared.f32 [%0+128], %2;\n"
                     "@p st.shared.f32 [%0+32], %3;\n@p st.shared.f32 [%0+160], %4;\n}" ::"r"(scw),
                     "f"(t1 ? c[1][0] : c[0][0]), "f"(t1 ? c[1][1] : c[0][1]), "f"(t1 ? c[1][2] : c[0][2]),
                     "f"(t1 ? c[1][3] : c[0][3]), "r"((uint32_t)mine) : "memory");
    }
    uint32_t a[8][4];
#pragma unroll
    for (int i = 0; i < 8; i++) ldsm4t(a[i], (va ^ ((i & 3) * 32)) + (i >> 2) * 8192);
    bar_c();
    float2 p0, p1, p2, p3;
    asm volatile("ld.shared.v2.f32 {%0,%1}, [%2];" : "=f"(p0.x), "=f"(p0.y) : "r"(scr) : "memory");
    asm volatile("ld.shared.v2.f32 {%0,%1}, [%2+512];" : "=f"(p1.x), "=f"(p1.y) : "r"(scr) : "memory");
    asm volatile("ld.shared.v2.f32 {%0,%1}, [%2+1024];" : "=f"(p2.x), "=f"(p2.y) : "r"(scr) : "memory");
    asm volatile("ld.shared.v2.f32 {%0,%1}, [%2+1536];" : "=f"(p3.x), "=f"(p3.y) : "r"(scr) : "memory");
    if (lb & 64) mbar_arrive(ebar);
    float m = sg ? s.m1 : s.m0, l = sg ? s.l1 : s.l0;
    const float s0 = ((p0.x + p1.x) + (p2.x + p3.x)) * SC;
    const float s1 = ((p0.y + p1.y) + (p2.y + p3.y)) * SC;
    float mx = fmaxf(s0, s1);
    if (__any_sync(0xffffffffu, mx > m)) {
        mx = fmaxf(mx, __shfl_xor_sync(0xffffffffu, mx, 1));
        mx = fmaxf(mx, __shfl_xor_sync(0xffffffffu, mx, 2));
        mx = fmaxf(mx, __shfl_xor_sync(0xffffffffu, mx, 4));
        mx = fmaxf(mx, __shfl_xor_sync(0xffffffffu, mx, 8));
        const float mn = fmaxf(mx, m);
        const float al = (mn == -INFINITY) ? 1.f : ex2(m - mn);
        float f0 = __shfl_sync(0xffffffffu, al, 0), f1 = __shfl_sync(0xffffffffu, al, 16);
        if (!mine) f0 = f1 = 1.f;
        l *= al;
        m = mn;
        if (sg) s.m1 = m; else s.m0 = m;
#pragma unroll
        for (int i = 0; i < 4; i++) {
            s.acc[4 * i + 0] *= f0; s.acc[4 * i + 1] *= f1;
            s.acc[4 * i + 2] *= f0; s.acc[4 * i + 3] *= f1;
        }
    }
    const uint32_t pk = pack_bf(ex2(s0 - m), ex2(s1 - m));
    uint32_t b[4];
    const bool col = ((lb & 32) != 0) == sg;
#pragma unroll
    for (int i = 0; i < 4; i++) {
        b[i] = __shfl_sync(0xffffffffu, pk, (lb & 31) + 4 * i);
        if (!col) b[i] = 0;
    }
    l += bf_lo(pk) + bf_hi(pk);
    if (sg) s.l1 = l; else s.l0 = l;
#pragma unroll
    for (int i = 0; i < 8; i++) mma16816(s.acc + 4 * (i & 3), a[i], b[(i >> 2) * 2], b[(i >> 2) * 2 + 1]);
}

__global__ void __launch_bounds__(512, 1)
fused_kernel(const __grid_constant__ CUtensorMap tmK, const __grid_constant__ CUtensorMap tmV,
             const __grid_constant__ CUtensorMap tmKs, const __grid_constant__ CUtensorMap tmVs, const Params P) {
    extern __shared__ __align__(1024) unsigned char smem[];
    const int tid = threadIdx.x;
    const int cta = blockIdx.x;
    const int G = gridDim.x;
    const uint32_t sb = smem_u32(smem);
    volatile int* meta = (volatile int*)(smem + OFF_META);
    volatile int* hslot = (volatile int*)(smem + OFF_HSLOT);

    if (tid == 0) {
        if (sb & 1023) __trap();
        for (int i = 0; i < NS; i++) {
            mbar_init(sb + OFF_FULL + i * 8, 1);
            mbar_init(sb + OFF_EMPTY + i * 8, 2);
        }
        for (int i = 0; i < NA; i++) mbar_init(sb + OFF_HREQ + i * 8, 1);
        for (int i = 0; i < 3; i++) mbar_init(sb + OFF_JB + i * 8, 1);
        asm volatile("fence.proxy.async.shared::cta;" ::: "memory");
    }
    __syncthreads();

    if (tid >= 128 && tid < 384) {
        asm volatile("setmaxnreg.inc.sync.aligned.u32 %0;" ::"n"(REG_H));
        const uint32_t so = sb + (tid - 128) * 16;
        uint4 r[NA * 8];
#pragma unroll
        for (int i = 0; i < NA * 8; i++) r[i] = make_uint4(0, 0, 0, 0);
#pragma unroll 1
        for (int pass = 0; pass < 2; pass++) {
#pragma unroll
            for (int i = 0; i < NA; i++) {
                mbar_wait(sb + OFF_HREQ + i * 8, pass);
                const int hs = hslot[i];
                const uint32_t so8 = hs & ~7;
                const uint32_t d = so + so8 * (SLOT / 8);
                if (pass == 0) {
                    mbar_wait(sb + OFF_FULL + so8, hs & 1);
#pragma unroll
                    for (int k = 0; k < 8; k++) {
                        uint4& v = r[i * 8 + k];
                        asm volatile("ld.shared.v4.u32 {%0,%1,%2,%3}, [%4];" : "=r"(v.x), "=r"(v.y), "=r"(v.z), "=r"(v.w) : "r"(d + k * 4096) : "memory");
                    }
                } else {
#pragma unroll
                    for (int k = 0; k < 8; k++) {
                        const uint4 v = r[i * 8 + k];
                        asm volatile("st.shared.v4.u32 [%0], {%1,%2,%3,%4};" ::"r"(d + k * 4096), "r"(v.x), "r"(v.y), "r"(v.z), "r"(v.w) : "memory");
                    }
                    asm volatile("fence.proxy.async.shared::cta;" ::: "memory");
                }
                asm volatile("bar.sync 2, 256;" ::: "memory");
                if (tid == 128) mbar_arrive(sb + (pass ? OFF_FULL : OFF_EMPTY) + so8);
            }
        }
    } else if (tid >= 384) {
        asm volatile("setmaxnreg.dec.sync.aligned.u32 24;");
        if (tid == 384) {
            volatile unsigned short* own = (volatile unsigned short*)(smem + OFF_OWN);
            const int TA0 = P.ta0;
            uint32_t pc = 0, wc = 0, lc = 0;
            int cn = 0;
            auto adv = [&](uint32_t& c) {
                c += 8;
                if ((c >> 3) == NS) c = (c & 1) ^ 1;
            };
            auto acquire = [&](int depth) {
                while ((cn >> 8) >= depth) {
                    mbar_wait(sb + OFF_FULL + (lc & ~7u), lc & 1);
                    adv(lc);
                    cn -= 256;
                }
                if ((cn & 255) == NS) {
                    mbar_wait(sb + OFF_EMPTY + (wc & ~7u), wc & 1);
                    adv(wc);
                    cn--;
                }
            };
            auto post = [&]() {
                adv(pc);
                cn += 257;
            };
            auto load_tile = [&](int tile, bool keep) {
                const uint32_t bar = sb + OFF_FULL + (pc & ~7u);
                const uint32_t dst = sb + (pc & ~7u) * (SLOT / 8);
                mbar_expect(bar, SLOT);
                if (!keep) {
                    tma4(dst, &tmK, tile * 4, bar, pol_first());
                    tma4(dst + 16384, &tmV, tile * 4, bar, pol_first());
                } else {
#pragma unroll
                    for (int o = 0; o < 16384; o += PIECE) {
                        tma4(dst + o, &tmKs, tile * 4 + (o >> 12), bar, pol_first());
                        tma4_prefetch(&tmKs, tile * 4 + (o >> 12), pol_normal());
                    }
#pragma unroll
                    for (int o = 0; o < 16384; o += PIECE) {
                        tma4(dst + 16384 + o, &tmVs, tile * 4 + (o >> 12), bar, pol_first());
                        tma4_prefetch(&tmVs, tile * 4 + (o >> 12), pol_normal());
                    }
                }
            };
            auto mark = [&](int m) {
                meta[pc >> 3] = m;
                mbar_arrive(sb + OFF_EMPTY + (pc & ~7u));
                mbar_arrive(sb + OFF_FULL + (pc & ~7u));
                post();
            };
            int hc = 0;
            auto main_flags = [&](int tile, int last) {
                const int head = tile >> 11;
                int m = head;
                if (head != (hc & 15)) { hc = head; m |= M_SVC; }
                else {
                    hc += 16;
                    if (hc == last + JCNT * 16) mbar_arrive(sb + OFF_JB);
                    if ((((hc >> 4) + cta) & 3) == 3 && hc >= 5 * 16) m |= M_SVC;
                }
                return m;
            };
            if (cta < 128) l2_prefetch((const char*)P.wq + cta * (DM * NQ * 2 / 128), DM * NQ * 2 / 128);
            unsigned nxt = ticket(0);
#pragma unroll 1
            for (int i = 0; i < NS; i++) {
                acquire(INITF);
                meta[pc >> 3] = 0;
                mbar_arrive(sb + OFF_EMPTY + (pc & ~7u));
                load_tile(cta + i * G, false);
                post();
            }
            int na = 0, nown = 0;
#pragma unroll 1
            while (true) {
                acquire(DEPTH_MAIN);
                int tile = (int)nxt + NS * G;
                bool isa = false;
                if (tile >= TA0) {
                    isa = na < NA;
                    tile = isa ? TA0 + na * G + cta : tile + G * NA;
                }
                if (tile >= NT) break;
                meta[pc >> 3] = main_flags(tile, 7);
                if (isa) {
                    hslot[na] = pc;
                    mbar_arrive(sb + OFF_HREQ + na * 8);
                    na++;
                    load_tile(tile, false);
                } else {
                    mbar_arrive(sb + OFF_EMPTY + (pc & ~7u));
                    if (tile >= OWN0) own[nown++] = (unsigned short)tile;
                    load_tile(tile, tile >= OWN0 && tile < P.tkeep);
                    nxt = nown < OWNCAP ? ticket(0) : (unsigned)NT;
                }
                post();
            }
            if ((hc & 15) != 7 || hc < 7 + JCNT * 16) mbar_arrive(sb + OFF_JB);
            mark(M_END | M_SVC | 7 | (0x77 << 16));
            nxt = ticket(1);
#pragma unroll 1
            for (int j = 0; j < NS; j++) {
                acquire(NS);
                const int back = j < NS - 1 ? NS - 1 - j : NS;
                mark(nown >= back ? (M_SIDE | M_USE1 | 7) : (M_NOP | M_SVC));
            }
            nown = nown > NS ? nown - NS : 0;
            na = 0;
            hc = 0;
            int np = 0;
#pragma unroll 1
            while (true) {
                const bool side_left = nown > 0 || na < NA;
                acquire(side_left ? NS : DEPTH_MAIN);
                bool side = side_left && np >= NSTAT2 && (np & 1);
                int tile = 0;
                if (!side) {
                    tile = np < NSTAT2 ? cta + np * G : (int)nxt + NSTAT2 * G;
                    if (tile >= TA0) tile = NT;
                    side = side_left && tile >= (nown > 0 ? 6 * TPH : NT);
                }
                mbar_arrive(sb + OFF_EMPTY + (pc & ~7u));
                if (side) {
                    if (nown > 0) {
                        meta[pc >> 3] = M_SIDE | M_USE1 | 7;
                        const int t4 = own[--nown] * 4;
                        const uint32_t bar = sb + OFF_FULL + (pc & ~7u);
                        const uint32_t dst = sb + (pc & ~7u) * (SLOT / 8);
                        mbar_expect(bar, SLOT);
                        tma4(dst, &tmK, t4, bar, pol_reread());
                        tma4(dst + 16384, &tmV, t4, bar, pol_reread());
                    } else {
                        meta[pc >> 3] = M_SIDE | M_USE1 | 6 | (na ? 0 : M_SVC);
                        hslot[na] = pc;
                        mbar_arrive(sb + OFF_HREQ + na * 8);
                        na++;
                    }
                } else if (tile < NT) {
                    meta[pc >> 3] = main_flags(tile, 6) | (tile >= 6 * TPH ? M_USE1 : 0);
                    load_tile(tile, false);
                    if (np >= NSTAT2) nxt = ticket(1);
                } else {
                    if ((hc & 15) != 6 || hc < 6 + JCNT * 16) mbar_arrive(sb + OFF_JB);
                    meta[pc >> 3] = M_END | M_SVC | 6 | (0x366 << 16);
                    mbar_arrive(sb + OFF_FULL + (pc & ~7u));
                    break;
                }
                np++;
                post();
            }
        } else if (tid >= 416 && tid < 448) {
            const int lane = tid - 416;
#pragma unroll 1
            for (int pass = 0; pass < 2; pass++) {
                mbar_wait(sb + OFF_JB, pass);
                int cta;
                asm volatile("mov.u32 %0, %ctaid.x;" : "=r"(cta));
                if (G - 1 - cta < 14) {
#pragma unroll 1
                    for (int i = lane; i < 1024; i += 32) st_pkt(g_ma + (G - 1 - cta) * 1024 + i, 0, 0, 0, 0);
                }
                if (cta < 128) {
#pragma unroll 1
                    for (int i = lane; i < 112; i += 32) st_pkt(g_mb + cta * 112 + i, 0, 0, 0, 0);
                    if (lane == 0) {
                        l2_prefetch((const char*)P.wo + ((7 - pass) * 128 + cta) * (4 * DM * 2), 4 * DM * 2);
                        l2_prefetch(g_rec + (size_t)((pass ^ 1) * 128 + cta) * G * 2, G * 32);
                    }
                }
                __threadfence();
                __syncwarp();
                if (lane == 0) {
                    mbar_arrive(sb + OFF_JB + 8);
                    mbar_wait(sb + OFF_JB + 16, pass);
                    asm volatile("mov.u32 %0, %ctaid.x;" : "=r"(cta));
                    if (cta < 128) {
                        l2_prefetch((const char*)P.w1 + cta * (DM * FF * 2 / 128), DM * FF * 2 / 128);
                        l2_prefetch((const char*)P.w2 + cta * (DM * FF * 2 / 128), DM * FF * 2 / 128);
                        if (!pass) l2_prefetch((const char*)P.wq + cta * (DM * NQ * 2 / 128), DM * NQ * 2 / 128);
                    }
                }
                __syncwarp();
            }
        }
    } else {
        asm volatile("setmaxnreg.dec.sync.aligned.u32 %0;" ::"n"(REG_C));
        float* sc = (float*)(smem + OFF_SC);
        float* red = (float*)(smem + OFF_RED);
        volatile uint2* xown = (volatile uint2*)(smem + OFF_XO);
        TS(0);
        uint32_t tagp;
        asm volatile("ld.relaxed.gpu.global.u32 %0, [%1];" : "=r"(tagp) : "l"(&g_epoch) : "memory");
        if (tid < 16) {
            const int own = G - 1 - cta;
            const __nv_bfloat16* p = own < 14 ? (tid < 8 ? P.x : P.b2) + own * 32 + (tid & 7) * 4
                                              : P.b1 + (cta < 112 ? cta : 0) * 16 + (tid & 3) * 4;
            const uint2 bv = ldg64(p);
            xown[tid].x = bv.x;
            xown[tid].y = bv.y;
        }
        __syncwarp();
        uint32_t rs = 2;

#pragma unroll 1
        while (true) {
            const bool first = rs & 2;
            if (cta < 128) {
                const int tid = tid_now();
                uint2 xp = make_uint2(0, 0);
                if (first) xp = ldg64(P.x + (tid < 112 ? tid : 0) * 4);
                uint4 wr[14];
                load_wq(wr, P.wq, cta, tid);
                if (first) {
                    tagp = (tagp + 1) << 5;
                } else {
                    xp = mb_poll(cta, tid, tagp | 11);
                    tagp |= 16;
                }
                TS(first ? 1 : 7);
                q_phase(wr, xp, sc, red, cta, tid, tagp | 15);
                TS(first ? 31 : 8);
            } else {
                tagp = first ? (tagp + 1) << 5 : tagp | 16;
            }
            rs &= ~2u;

            St st;
#pragma unroll
            for (int i = 0; i < 16; i++) st.acc[i] = 0.f;
            st.m0 = st.m1 = -INFINITY;
            st.l0 = st.l1 = 0.f;
            float xacc[4] = {0.f, 0.f, 0.f, 0.f};
            uint32_t lds_k, lds_v, scw, scr, src;
            {
                const int t = tid_now();
                const int lane = t & 31, w = t >> 5;
                lds_k = sb + w * 1024 + ((lane >> 3) & 1) * 4096 + (lane & 7) * 128 + (((lane >> 4) ^ (lane & 7)) << 4);
                lds_v = sb + 16384 + w * 1024 + (lane >> 4) * 4096 + (lane & 7) * 128 + ((((lane >> 3) & 1) ^ (lane & 7)) << 4);
                scw = sb + OFF_SC + w * 512 + ((lane & 1) * 16 + (lane >> 2)) * 4;
                scr = sb + OFF_SC + lane * 8;
                src = ((lane >> 2) & 1) * 16 + (lane & 3) + (lane >> 4) * 32 + (t == 0 ? 64 : 0);
                asm volatile("" : "+r"(lds_k), "+r"(lds_v), "+r"(scw), "+r"(scr), "+r"(src));
            }
            st_loadq(st, 0, 7, tagp | 15);
            TS(2 + ((tagp >> 4) & 1) * 10);
            int bk = 0;

#pragma unroll 1
            while (true) {
                mbar_wait(sb + OFF_FULL + (rs & ~7u), rs & 1);
                const int mt = meta[rs >> 3];
                if (mt & M_SVC) {
                    if ((mt & M_END) && (bk & 0x3ff) == (mt >> 16)) break;
                    asm volatile("" : "+r"(tagp));
                    const int pass = (tagp >> 4) & 1;
                    const int head = mt & 15;
                    if (pass && !(bk & 512) && head >= 6) {
                        TS(60);
                        st_flush(st, 1, 2, G, cta, tagp | 7);
                        bk |= 512;
                        st_loadq(st, bk & 7, 6, tagp | 15);
                    }
                    if (!(mt & (M_SIDE | M_NOP))) {
                        const bool adv = head != (bk & 15) || (mt & M_END);
#pragma unroll 1
                        while (true) {
                            const int cur = bk & 15, ncomb = (bk >> 4) & 15;
                            int ch;
                            if (ncomb == cur && cur < head) {
                                st_flush(st, 0, cur & 1, G, cta, tagp | cur);
                                bk++;
                                if (cur + 1 == head && !(mt & M_END)) break;
                                continue;
                            }
                            if (pass && !(bk & 256) && ncomb == cur && ((mt & M_END) || (!adv && cur >= 2))) ch = 7;
                            else if (ncomb < cur) ch = ncomb;
                            else break;
                            const bool s7 = pass && ch == 7;
                            const bool ok = combine(adv, xacc, ch, s7 ? 2 : (ch & 1), G, cta, tagp | ch, P.wo, red + (bk & 1024 ? 32 : 0));
                            bk ^= 1024;
                            if (ok) bk += s7 ? 256 : 16;
                            if (!adv) break;
                        }
                        if (adv && !(mt & (M_USE1 | M_END))) st_loadq(st, head, (bk & 512) ? 6 : 7, tagp | 15);
                    }
                    if (mt & (M_NOP | M_END)) {
                        if (mt & M_END) break;
                        bar_c();
                        if (src & 64) mbar_arrive(sb + OFF_EMPTY + (rs & ~7u));
                        rs += 8;
                        if ((rs >> 3) == NS) rs = (rs & 1) ^ 1;
                        continue;
                    }
                }
                const uint32_t tb = (rs & ~7u) * (SLOT / 8);
                const uint32_t ebar = sb + OFF_EMPTY + (rs & ~7u);
                tile_step(st, (mt & M_USE1) != 0, lds_k + tb, lds_v + tb, scw, scr, src, ebar);
                scw ^= 256;
                scr ^= 256;
                rs += 8;
                if ((rs >> 3) == NS) rs = (rs & 1) ^ 1;
            }
            TS(40 + ((tagp >> 4) & 1) * 15);

            asm volatile("" : "+r"(tagp));
            const int pass = (tagp >> 4) & 1;
            const int tid = tid_now();
            const int lane = tid & 31, w = tid >> 5;
            mbar_wait(sb + OFF_JB + 8, pass);
            st_flush(st, pass, pass ^ 1, G, cta, tagp | (7 - pass));
            if (cta < 128) combine(true, xacc, 7 - pass, pass ^ 1, G, cta, tagp | (7 - pass), P.wo, red + 64);
            TS(3 + pass * 10);
            if (tid < 112 && cta < 128) st_pkt4(g_ma + ((tid >> 3) * 128 + cta) * 8 + (tid & 7), xacc, tagp | 8);
            if (cta >= 128) bar_c();
            if (tid == 127) {
                mbar_arrive(sb + OFF_JB + 16);
                mbar_arrive(sb + OFF_EMPTY + (rs & ~7u));
            }
            rs += 8;
            if ((rs >> 3) == NS) rs = (rs & 1) ^ 1;
            __syncwarp();
            TS(pass ? 14 : 4);
            const int own = G - 1 - cta;
            if (own < 14) {
#pragma unroll 1
                for (int stage = 0; stage < 2; stage++) {
                    const uint32_t tg = tagp | (8 + 2 * stage);
                    const uint4* p = g_ma + own * 1024 + tid;
                    uint4 a[8];
                    int it = 0;
                    while (true) {
#pragma unroll
                        for (int k = 0; k < 7; k++) a[k] = ld_pkt(p + k * 128);
                        a[7] = ld_pkt(p + (stage ? 0 : 7 * 128));
                        bool ok = true;
#pragma unroll
                        for (int k = 0; k < 8; k++) ok = ok && pkt4_tag(a[k]) == tg;
                        if (__all_sync(0xffffffffu, ok)) break;
                        if (++it > SPIN_MAX) __trap();
                    }
                    if (stage) a[7] = make_uint4(0, 0, 0, 0);
                    float v[4];
#define SUM8(c) (((__uint_as_float(a[0].c) + __uint_as_float(a[1].c)) + (__uint_as_float(a[2].c) + __uint_as_float(a[3].c))) + \
                 ((__uint_as_float(a[4].c) + __uint_as_float(a[5].c)) + (__uint_as_float(a[6].c) + __uint_as_float(a[7].c))))
                    v[0] = SUM8(x); v[1] = SUM8(y); v[2] = SUM8(z); v[3] = SUM8(w);
#undef SUM8
                    {
                        const bool up = lane & 16;
                        v[0] = (up ? v[2] : v[0]) + __shfl_xor_sync(0xffffffffu, up ? v[0] : v[2], 16);
                        v[1] = (up ? v[3] : v[1]) + __shfl_xor_sync(0xffffffffu, up ? v[1] : v[3], 16);
                    }
                    {
                        const bool up = lane & 8;
                        v[0] = (up ? v[1] : v[0]) + __shfl_xor_sync(0xffffffffu, up ? v[0] : v[1], 8);
                    }
                    float* rb = sc + stage * 128;
                    rb[w * 32 + (lane & 7) * 4 + (lane >> 4) * 2 + ((lane >> 3) & 1)] = v[0];
                    const uint32_t xo0 = xown[tid & 7].x, xo1 = xown[tid & 7].y;
                    const uint32_t b20 = stage ? xown[8 + (tid & 7)].x : 0u, b21 = stage ? xown[8 + (tid & 7)].y : 0u;
                    bar_c();
                    TS(stage ? (pass ? 24 : 10) : (pass ? 23 : 9));
                    uint2 xn;
                    {
                        const float* rp = rb + (tid & 7) * 4;
                        const float4 r0 = *(const float4*)(rp), r1 = *(const float4*)(rp + 32);
                        const float4 r2 = *(const float4*)(rp + 64), r3 = *(const float4*)(rp + 96);
                        float t0 = bfr((r0.x + r1.x) + (r2.x + r3.x)), t1 = bfr((r0.y + r1.y) + (r2.y + r3.y));
                        float t2 = bfr((r0.z + r1.z) + (r2.z + r3.z)), t3 = bfr((r0.w + r1.w) + (r2.w + r3.w));
                        xn.x = pack_bf(bf_lo(xo0) + bfr(t0 + bf_lo(b20)), bf_hi(xo0) + bfr(t1 + bf_hi(b20)));
                        xn.y = pack_bf(bf_lo(xo1) + bfr(t2 + bf_lo(b21)), bf_hi(xo1) + bfr(t3 + bf_hi(b21)));
                    }
                    if (stage && pass) {
                        if (tid < 8) *(uint2*)(P.out + own * 32 + tid * 4) = xn;
                        TS(17);
                        break;
                    }
                    uint4* pp = g_mb + (tid >> 3) * 112 + own * 8 + (tid & 7);
#pragma unroll
                    for (int k = 0; k < 7; k++) st_pkt(pp + k * 16 * 112, xn.x, xn.y, tg | 1, tg | 1);
                    if (stage) st_pkt(pp + 7 * 16 * 112, xn.x, xn.y, tg | 1, tg | 1);
                    if (tid < 8) { xown[tid].x = xn.x; xown[tid].y = xn.y; }
                    if (tid == 0 && own == 0 && !stage) {
                        if (pass) { g_ctr1[0] = 0; g_epoch = tagp >> 5; }
                        else g_ctr0[0] = 0;
                    }
                    bar_c();
                }
            } else if (cta < 112) {
                uint4 w1r[7];
                uint2 w2r[16];
                {
                    const uint64_t pol = pol_first();
                    const __nv_bfloat16* p1 = P.w1 + (size_t)(tid >> 1) * FF + cta * 16 + (tid & 1) * 8;
#pragma unroll
                    for (int r = 0; r < 7; r++) w1r[r] = ldg128(p1 + (size_t)r * 64 * FF, pol);
                    const __nv_bfloat16* p2 = P.w2 + (size_t)cta * 16 * DM + (tid < 112 ? tid : 0) * 4;
#pragma unroll
                    for (int r = 0; r < 16; r++) w2r[r] = ldg64p(p2 + r * DM, pol);
                }
                TS(pass ? 25 : 18);
                const uint2 xp = mb_poll(cta, tid, tagp | 9);
                TS(5 + pass * 10);
                float mean, sd;
                ln_stats(xp, sc, tid, mean, sd);
                float s[8];
#pragma unroll
                for (int i = 0; i < 8; i++) s[i] = 0.f;
#pragma unroll
                for (int r = 0; r < 7; r++) fma8(s, ln_apply(sc[(tid >> 1) + 64 * r], mean, sd), w1r[r]);
                {
                    const bool up = lane & 16;
#pragma unroll
                    for (int i = 0; i < 4; i++) {
                        float send = up ? s[i] : s[i + 4];
                        float keep = up ? s[i + 4] : s[i];
                        s[i] = keep + __shfl_xor_sync(0xffffffffu, send, 16);
                    }
                }
                {
                    const bool up = lane & 8;
#pragma unroll
                    for (int i = 0; i < 2; i++) {
                        float send = up ? s[i] : s[i + 2];
                        float keep = up ? s[i + 2] : s[i];
                        s[i] = keep + __shfl_xor_sync(0xffffffffu, send, 8);
                    }
                }
                {
                    const bool up = lane & 4;
                    float send = up ? s[0] : s[1];
                    float keep = up ? s[1] : s[0];
                    s[0] = keep + __shfl_xor_sync(0xffffffffu, send, 4);
                }
                s[0] += __shfl_xor_sync(0xffffffffu, s[0], 2);
                const int col = (lane & 1) * 8 + ((lane >> 4) & 1) * 4 + ((lane >> 3) & 1) * 2 + ((lane >> 2) & 1);
                if (!(lane & 2)) red[w * 16 + col] = s[0];
                bar_c();
                const int c = lane & 15;
                float hv = (red[c] + red[16 + c]) + (red[32 + c] + red[48 + c]);
                hv = bfr(gelu_tanh(bfr(bfr(hv) + __bfloat162float(((const __nv_bfloat16*)(smem + OFF_XO))[c]))));
                xacc[0] = xacc[1] = xacc[2] = xacc[3] = 0.f;
#pragma unroll
                for (int r = 0; r < 16; r++) {
                    const float g = __shfl_sync(0xffffffffu, hv, r);
                    xacc[0] += g * bf_lo(w2r[r].x);
                    xacc[1] += g * bf_hi(w2r[r].x);
                    xacc[2] += g * bf_lo(w2r[r].y);
                    xacc[3] += g * bf_hi(w2r[r].y);
                }
                if (tid < 112) st_pkt4(g_ma + ((tid >> 3) * 128 + cta) * 8 + (tid & 7), xacc, tagp | 10);
                TS(pass ? 16 : 6);
            }
            if (tagp & 16) break;
        }
    }
}

typedef CUresult (*EncodeFn)(CUtensorMap*, CUtensorMapDataType, cuuint32_t, void*, const cuuint64_t*, const cuuint64_t*,
                             const cuuint32_t*, const cuuint32_t*, CUtensorMapInterleave, CUtensorMapSwizzle,
                             CUtensorMapL2promotion, CUtensorMapFloatOOBfill);

void make_map(EncodeFn fn, CUtensorMap* tm, const void* p, int box_bytes) {
    cuuint64_t dims[4] = {64, 8, 4, 65536};
    cuuint64_t str[3] = {512, 128, 4096};
    cuuint32_t box[4] = {64, 8, 4, (cuuint32_t)(box_bytes / 4096)};
    cuuint32_t es[4] = {1, 1, 1, 1};
    fn(tm, CU_TENSOR_MAP_DATA_TYPE_BFLOAT16, 4, (void*)p, dims, str, box, es, CU_TENSOR_MAP_INTERLEAVE_NONE,
       CU_TENSOR_MAP_SWIZZLE_128B, CU_TENSOR_MAP_L2_PROMOTION_NONE, CU_TENSOR_MAP_FLOAT_OOB_FILL_NONE);
}

}

extern "C" void kernel_launch(void* const* d_in, const int* in_sizes, int n_in, void* d_out, int out_size) {
    static EncodeFn enc = nullptr;
    static int nsm = 0;
    if (!enc) {
        void* fn = nullptr;
        cudaDriverEntryPointQueryResult qr;
        cudaGetDriverEntryPoint("cuTensorMapEncodeTiled", &fn, cudaEnableDefault, &qr);
        enc = (EncodeFn)fn;
        int dev = 0;
        cudaGetDevice(&dev);
        cudaDeviceGetAttribute(&nsm, cudaDevAttrMultiProcessorCount, dev);
        cudaFuncSetAttribute(fused_kernel, cudaFuncAttributeMaxDynamicSharedMemorySize, SMEM_TOTAL);
    }
    Params P;
    P.x = (const __nv_bfloat16*)d_in[0];
    P.k = (const __nv_bfloat16*)d_in[1];
    P.v = (const __nv_bfloat16*)d_in[2];
    P.wq = (const __nv_bfloat16*)d_in[3];
    P.wo = (const __nv_bfloat16*)d_in[4];
    P.w1 = (const __nv_bfloat16*)d_in[6];
    P.b1 = (const __nv_bfloat16*)d_in[7];
    P.w2 = (const __nv_bfloat16*)d_in[8];
    P.b2 = (const __nv_bfloat16*)d_in[9];
    P.out = (__nv_bfloat16*)d_out;
    P.ta0 = OWN0 - nsm * NA;
    P.tkeep = NT - nsm * NS;
    CUtensorMap tmK, tmV, tmKs, tmVs;
    make_map(enc, &tmK, P.k, 16384);
    make_map(enc, &tmV, P.v, 16384);
    make_map(enc, &tmKs, P.k, PIECE);
    make_map(enc, &tmVs, P.v, PIECE);
    fused_kernel<<<nsm, 512, SMEM_TOTAL>>>(tmK, tmV, tmKs, tmVs, P);
}
```

```cpp
#include <cuda_runtime.h>
#include <cuda_bf16.h>
#include <cuda.h>
#include <stdint.h>
#include <limits.h>

namespace {

constexpr int DM = 448;
constexpr int FF = 1792;
constexpr int NQ = 4096;
constexpr int TPH = 2048;
constexpr int NT = 8 * TPH;
constexpr int OWN0 = 7 * TPH;
constexpr int NS = 7;
constexpr int NA = 6;
constexpr int DEPTH = 2;
constexpr int DEPTH_MIX = 4;
constexpr int NSTAT = 2;
constexpr int PIECE = 4096;
constexpr int JCNT = 5;
constexpr int PF_DELAY_W = 1000;
constexpr int PF_DELAY_T = 3000;
constexpr int PF_PACE = 1350;
constexpr int REG_H = NA * 32 + 8, REG_C = 88, REG_P = 24;
static_assert(2 * REG_H + REG_C + REG_P <= 512, "register file");
constexpr bool FOLD_Q = false, FOLD_M = true;
constexpr int SLOT = 32768;
constexpr int MAXG = 144;
constexpr int OWNCAP = 32;
constexpr int SPIN_MAX = 1 << 22;

constexpr int M_USE1 = 1 << 8;
constexpr int M_SVC = 1 << 9;
constexpr int M_SIDE = 1 << 10;
constexpr int M_END = 1 << 11;
constexpr int M_NOP = 1 << 12;
constexpr int M_SW = 1 << 13;

constexpr int OFF_SC = NS * SLOT;
constexpr int OFF_RED = OFF_SC + 2048;
constexpr int OFF_FULL = OFF_RED + 512;
constexpr int OFF_EMPTY = OFF_FULL + 64;
constexpr int OFF_HREQ = OFF_EMPTY + 64;
constexpr int OFF_META = OFF_HREQ + 64;
constexpr int OFF_HSLOT = OFF_META + 32;
constexpr int OFF_JB = OFF_HSLOT + 32;
constexpr int OFF_XO = OFF_JB + 32;
constexpr int OFF_OWN = OFF_XO + 128;
constexpr int SMEM_TOTAL = OFF_OWN + OWNCAP * 2;
static_assert(SMEM_TOTAL <= 232448, "smem");
static_assert(NS <= 7 && NA <= 6, "bars");

__device__ __align__(128) uint4 g_rec[3 * 128 * MAXG * 2];
__device__ __align__(128) uint4 g_q[1024];
__device__ __align__(128) uint4 g_ma[14 * 128 * 8];
__device__ __align__(128) uint4 g_mb[128 * 112];
__device__ __align__(128) unsigned g_ctr0[32];
__device__ __align__(128) unsigned g_ctr1[32];
__device__ unsigned g_epoch;

__device__ __forceinline__ uint32_t smem_u32(const void* p) { return (uint32_t)__cvta_generic_to_shared(p); }
__device__ __forceinline__ int tid_now() {
    int t;
    asm volatile("mov.u32 %0, %tid.x;" : "=r"(t));
    return t;
}
__device__ __forceinline__ uint64_t pol_first() {
    uint64_t p;
    asm volatile("createpolicy.fractional.L2::evict_first.b64 %0, 1.0;" : "=l"(p));
    return p;
}
__device__ __forceinline__ uint64_t pol_normal() {
    uint64_t p;
    asm volatile("createpolicy.fractional.L2::evict_normal.b64 %0, 1.0;" : "=l"(p));
    return p;
}
__device__ __forceinline__ void mbar_init(uint32_t bar, int cnt) {
    asm volatile("mbarrier.init.shared.b64 [%0], %1;" ::"r"(bar), "r"(cnt) : "memory");
}
__device__ __forceinline__ void mbar_expect(uint32_t bar, uint32_t bytes) {
    asm volatile("mbarrier.arrive.expect_tx.shared.b64 _, [%0], %1;" ::"r"(bar), "r"(bytes) : "memory");
}
__device__ __forceinline__ void mbar_arrive(uint32_t bar) {
    asm volatile("mbarrier.arrive.shared.b64 _, [%0];" ::"r"(bar) : "memory");
}
__device__ __forceinline__ void mbar_wait(uint32_t bar, uint32_t parity) {
    int it = 0;
    while (true) {
        uint32_t ok;
        asm volatile("{\n.reg .pred p;\nmbarrier.try_wait.parity.shared.b64 p, [%1], %2;\nselp.u32 %0, 1, 0, p;\n}"
                     : "=r"(ok) : "r"(bar), "r"(parity) : "memory");
        if (ok) break;
        if (++it > SPIN_MAX) __trap();
    }
}
__device__ __forceinline__ void tma4(uint32_t dst, const CUtensorMap* tm, int c3, uint32_t bar, uint64_t pol) {
    asm volatile(
        "cp.async.bulk.tensor.4d.shared::cluster.global.mbarrier::complete_tx::bytes.L2::cache_hint "
        "[%0], [%1, {%3,%3,%3,%4}], [%2], %5;" ::"r"(dst), "l"(tm), "r"(bar), "r"(0), "r"(c3), "l"(pol) : "memory");
}
__device__ __forceinline__ void tma2(uint32_t dst, const CUtensorMap* tm, int c0, int c1, uint32_t bar) {
    asm volatile(
        "cp.async.bulk.tensor.2d.shared::cluster.global.mbarrier::complete_tx::bytes "
        "[%0], [%1, {%3,%4}], [%2];" ::"r"(dst), "l"(tm), "r"(bar), "r"(c0), "r"(c1) : "memory");
}
__device__ __forceinline__ void tma4_prefetch_plain(const CUtensorMap* tm, int c3) {
    asm volatile("cp.async.bulk.prefetch.tensor.4d.L2.global [%0, {%1,%1,%1,%2}];" ::"l"(tm), "r"(0), "r"(c3) : "memory");
}
__device__ __forceinline__ uint32_t timer_lo() {
    uint32_t t;
    asm volatile("mov.u32 %0, %globaltimer_lo;" : "=r"(t));
    return t;
}
__device__ __forceinline__ void tma4_prefetch(const CUtensorMap* tm, int c3, uint64_t pol) {
    asm volatile("cp.async.bulk.prefetch.tensor.4d.L2.global.L2::cache_hint [%0, {%1,%1,%1,%2}], %3;" ::"l"(tm), "r"(0), "r"(c3), "l"(pol) : "memory");
}
__device__ __forceinline__ unsigned ticket(int which) {
    unsigned r;
    if (which) asm volatile("atom.relaxed.gpu.global.add.u32 %0, [%1], 1;" : "=r"(r) : "l"(g_ctr1) : "memory");
    else asm volatile("atom.relaxed.gpu.global.add.u32 %0, [%1], 1;" : "=r"(r) : "l"(g_ctr0) : "memory");
    return r;
}
__device__ __forceinline__ void l2_prefetch(const void* src, uint32_t bytes) {
    asm volatile("cp.async.bulk.prefetch.L2.global [%0], %1;" ::"l"(src), "r"(bytes) : "memory");
}
__device__ __forceinline__ void bar_c() { asm volatile("bar.sync 1, 128;" ::: "memory"); }
__device__ __forceinline__ bool bar_c_and(bool v) {
    uint32_t r;
    asm volatile("{\n.reg .pred p, q;\nsetp.ne.u32 q, %1, 0;\nbar.red.and.pred p, 3, 128, q;\nselp.u32 %0, 1, 0, p;\n}"
                 : "=r"(r) : "r"((uint32_t)v) : "memory");
    return r != 0;
}
__device__ __forceinline__ void ldsm4(uint32_t* r, uint32_t a) {
    asm volatile("ldmatrix.sync.aligned.m8n8.x4.shared.b16 {%0,%1,%2,%3}, [%4];"
                 : "=r"(r[0]), "=r"(r[1]), "=r"(r[2]), "=r"(r[3]) : "r"(a) : "memory");
}
__device__ __forceinline__ void ldsm4t(uint32_t* r, uint32_t a) {
    asm volatile("ldmatrix.sync.aligned.m8n8.x4.trans.shared.b16 {%0,%1,%2,%3}, [%4];"
                 : "=r"(r[0]), "=r"(r[1]), "=r"(r[2]), "=r"(r[3]) : "r"(a) : "memory");
}
__device__ __forceinline__ void mma16816(float* c, const uint32_t* a, uint32_t b0, uint32_t b1) {
    asm volatile("mma.sync.aligned.m16n8k16.row.col.f32.bf16.bf16.f32 {%0,%1,%2,%3}, {%4,%5,%6,%7}, {%8,%9}, {%0,%1,%2,%3};"
                 : "+f"(c[0]), "+f"(c[1]), "+f"(c[2]), "+f"(c[3])
                 : "r"(a[0]), "r"(a[1]), "r"(a[2]), "r"(a[3]), "r"(b0), "r"(b1));
}
__device__ __forceinline__ void st_pkt(void* p, uint32_t a, uint32_t b, uint32_t c, uint32_t d) {
    asm volatile("{\n.reg .b128 v;\n.reg .b64 lo, hi;\nmov.b64 lo, {%1,%2};\nmov.b64 hi, {%3,%4};\nmov.b128 v, {lo,hi};\n"
                 "st.relaxed.gpu.global.b128 [%0], v;\n}" ::"l"(p), "r"(a), "r"(b), "r"(c), "r"(d) : "memory");
}
__device__ __forceinline__ uint4 ld_pkt(const void* p) {
    uint4 r;
    asm volatile("{\n.reg .b128 v;\n.reg .b64 lo, hi;\nld.relaxed.gpu.global.b128 v, [%4];\nmov.b128 {lo,hi}, v;\n"
                 "mov.b64 {%0,%1}, lo;\nmov.b64 {%2,%3}, hi;\n}"
                 : "=r"(r.x), "=r"(r.y), "=r"(r.z), "=r"(r.w) : "l"(p) : "memory");
    return r;
}
__device__ __forceinline__ void st_pkt4(void* p, const float* v, uint32_t tag) {
    st_pkt(p, __byte_perm(__float_as_uint(v[0]), tag, 0x3214), __float_as_uint(v[1]), __float_as_uint(v[2]), __float_as_uint(v[3]));
}
__device__ __forceinline__ uint4 ldg128(const void* p, uint64_t pol) {
    uint4 r;
    asm volatile("ld.global.nc.L2::cache_hint.v4.u32 {%0,%1,%2,%3}, [%4], %5;"
                 : "=r"(r.x), "=r"(r.y), "=r"(r.z), "=r"(r.w) : "l"(p), "l"(pol) : "memory");
    return r;
}
__device__ __forceinline__ uint32_t ldg32p(const void* p, uint64_t pol) {
    uint32_t r;
    asm volatile("ld.global.nc.L2::cache_hint.u32 %0, [%1], %2;" : "=r"(r) : "l"(p), "l"(pol) : "memory");
    return r;
}
__device__ __forceinline__ uint2 ldg64p(const void* p, uint64_t pol) {
    uint2 r;
    asm volatile("ld.global.nc.L2::cache_hint.v2.u32 {%0,%1}, [%2], %3;" : "=r"(r.x), "=r"(r.y) : "l"(p), "l"(pol) : "memory");
    return r;
}
__device__ __forceinline__ uint2 ldg64(const void* p) {
    uint2 r;
    asm volatile("ld.global.nc.v2.u32 {%0,%1}, [%2];" : "=r"(r.x), "=r"(r.y) : "l"(p) : "memory");
    return r;
}
__device__ __forceinline__ float bf_lo(uint32_t u) { return __uint_as_float(u << 16); }
__device__ __forceinline__ float bf_hi(uint32_t u) { return __uint_as_float(u & 0xffff0000u); }
__device__ __forceinline__ uint32_t pack_bf(float lo, float hi) {
    uint32_t r;
    asm("cvt.rn.bf16x2.f32 %0, %1, %2;" : "=r"(r) : "f"(hi), "f"(lo));
    return r;
}
__device__ __forceinline__ float rcp(float x) {
    float r;
    asm("rcp.approx.ftz.f32 %0, %1;" : "=f"(r) : "f"(x));
    return r;
}
__device__ __forceinline__ float warp_max(float x) {
    int k = __float_as_int(x);
    k ^= (k >> 31) & 0x7fffffff;
    k = __reduce_max_sync(0xffffffffu, k);
    k ^= (k >> 31) & 0x7fffffff;
    return __int_as_float(k);
}
__device__ __forceinline__ float bfr(float x) { return __uint_as_float(pack_bf(0.f, x)); }
__device__ __forceinline__ float ex2(float x) {
    float r;
    asm("ex2.approx.ftz.f32 %0, %1;" : "=f"(r) : "f"(x));
    return r;
}

struct St {
    float acc[16];
    uint32_t q[8];
    float m0, l0, m1, l1;
};

struct Params {
    const __nv_bfloat16 *x, *k, *v, *wq, *wo, *w1, *b1, *w2, *b2;
    __nv_bfloat16* out;
    int ta0;
    int tk0, tkeep;
};

__device__ __forceinline__ void st_loadq(St& s, int h0, int h1, uint32_t tag) {
    const int tid = tid_now();
    const int lane = tid & 31, w = tid >> 5;
    const int h = lane < 16 ? h0 : h1;
    const uint4* p = g_q + (((2 * h + ((lane >> 2) & 1)) * 4 + w) * 16 + (lane & 3));
    p += lane & 8;
    int it = 0;
    uint4 a, b;
    while (true) {
        a = ld_pkt(p);
        b = ld_pkt(p + 4);
        if (__all_sync(0xffffffffu, a.z == tag && b.z == tag)) break;
        if (++it > SPIN_MAX) __trap();
    }
    const uint32_t o0 = __shfl_xor_sync(0xffffffffu, a.x, 8), o1 = __shfl_xor_sync(0xffffffffu, a.y, 8);
    const uint32_t o2 = __shfl_xor_sync(0xffffffffu, b.x, 8), o3 = __shfl_xor_sync(0xffffffffu, b.y, 8);
    const bool up = lane & 8;
    s.q[0] = up ? o0 : a.x; s.q[1] = up ? o1 : a.y; s.q[2] = up ? o2 : b.x; s.q[3] = up ? o3 : b.y;
    s.q[4] = up ? a.x : o0; s.q[5] = up ? a.y : o1; s.q[6] = up ? b.x : o2; s.q[7] = up ? b.y : o3;
}

__device__ __forceinline__ void st_flush(St& s, int sg, int buf, int cta, uint32_t tag) {
    const int tid = tid_now();
    const int u = tid & 1;
    uint4* p = g_rec + ((buf * 128 + (tid & ~3)) * MAXG + cta) * 2 + u;
    asm volatile("" : "+l"(p));
    float l = sg ? s.l1 : s.l0;
    l += __shfl_xor_sync(0xffffffffu, l, 1);
    l += __shfl_xor_sync(0xffffffffu, l, 2);
    l += __shfl_xor_sync(0xffffffffu, l, 4);
    l += __shfl_xor_sync(0xffffffffu, l, 8);
    const float y = u ? l : (sg ? s.m1 : s.m0);
    const float yo = __shfl_xor_sync(0xffffffffu, y, 16);
    const bool hi = tid & 16;
    const float ml[2] = {hi ? yo : y, hi ? y : yo};
    const bool mine = ((tid >> 1) & 1) == sg;
#pragma unroll
    for (int r = 0; r < 4; r++) {
        const int o = (r & 1) * 2 + (r >> 1);
        asm volatile("{\n.reg .pred p;\n.reg .b128 v;\n.reg .b64 lo, hi;\nsetp.ne.u32 p, %5, 0;\nmov.b64 lo, {%1,%2};\nmov.b64 hi, {%3,%4};\n"
                     "mov.b128 v, {lo,hi};\n@p st.relaxed.gpu.global.b128 [%0], v;\n}" ::"l"(p + r * MAXG * 2),
                     "f"(u ? s.acc[8 + o] : s.acc[o]), "f"(u ? s.acc[12 + o] : s.acc[4 + o]), "f"(ml[r >> 1]), "r"(tag),
                     "r"((uint32_t)mine) : "memory");
    }
#pragma unroll
    for (int i = 0; i < 16; i++) s.acc[i] = mine ? 0.f : s.acc[i];
    if (sg) { s.m1 = -INFINITY; s.l1 = 0.f; }
    else { s.m0 = -INFINITY; s.l0 = 0.f; }
}

__device__ __forceinline__ bool combine(bool block, float* on, int buf, int G, int cta, uint32_t tag, float* red) {
    const int tid = tid_now();
    const int j = cta & 127;
    const uint4* p = g_rec + ((buf * 128 + j) * MAXG + tid) * 2;
    const bool two = tid + 128 < G;
    const uint4* p2 = two ? p + 256 : p;
    float s[5], m1;
    {
        uint4 a, b, c, d;
        int it = 0;
        bool ok;
        while (true) {
            a = ld_pkt(p);
            b = ld_pkt(p + 1);
            c = ld_pkt(p2);
            d = ld_pkt(p2 + 1);
            ok = __all_sync(0xffffffffu, a.w == tag && b.w == tag && c.w == tag && d.w == tag);
            if (ok || !block) break;
            if (++it > SPIN_MAX) __trap();
        }
        if (!block) {
            if (!bar_c_and(ok)) return false;
        }
        const float ma = __uint_as_float(a.z), mb = two ? __uint_as_float(c.z) : -INFINITY;
        m1 = warp_max(fmaxf(ma, mb));
        const float ms = (m1 == -INFINITY) ? 0.f : m1;
        const float f1 = ex2(ma - ms), f2 = ex2(mb - ms);
        s[0] = f1 * __uint_as_float(a.x) + f2 * __uint_as_float(c.x);
        s[1] = f1 * __uint_as_float(a.y) + f2 * __uint_as_float(c.y);
        s[2] = f1 * __uint_as_float(b.x) + f2 * __uint_as_float(d.x);
        s[3] = f1 * __uint_as_float(b.y) + f2 * __uint_as_float(d.y);
        s[4] = f1 * __uint_as_float(b.z) + f2 * __uint_as_float(d.z);
    }
#pragma unroll
    for (int o = 16; o > 0; o >>= 1) {
#pragma unroll
        for (int i = 0; i < 5; i++) s[i] += __shfl_xor_sync(0xffffffffu, s[i], o);
    }
    if ((tid & 31) == 0) {
        *(float4*)(red + (tid >> 5) * 8) = make_float4(s[0], s[1], s[2], s[3]);
        *(float2*)(red + (tid >> 5) * 8 + 4) = make_float2(s[4], m1);
    }
    bar_c();
    float M = -INFINITY;
#pragma unroll
    for (int i = 0; i < 4; i++) M = fmaxf(M, red[i * 8 + 5]);
    float o4[4] = {0.f, 0.f, 0.f, 0.f}, L = 0.f;
#pragma unroll
    for (int i = 0; i < 4; i++) {
        float4 v = *(const float4*)(red + i * 8);
        float2 lm = *(const float2*)(red + i * 8 + 4);
        float f = ex2(lm.y - M);
        o4[0] += f * v.x; o4[1] += f * v.y; o4[2] += f * v.z; o4[3] += f * v.w;
        L += f * lm.x;
    }
    const float inv = rcp(L);
#pragma unroll
    for (int i = 0; i < 4; i++) on[i] = bfr(o4[i] * inv);
    return true;
}

__device__ __forceinline__ float2 ln_partial(uint2 xp, int lane) {
    const float sh = bf_lo(__shfl_sync(0xffffffffu, xp.x, 0));
    const float d0 = bf_lo(xp.x) - sh, d1 = bf_hi(xp.x) - sh, d2 = bf_lo(xp.y) - sh, d3 = bf_hi(xp.y) - sh;
    float s = lane < 28 ? (d0 + d1) + (d2 + d3) : 0.f;
    float q = lane < 28 ? (d0 * d0 + d1 * d1) + (d2 * d2 + d3 * d3) : 0.f;
#pragma unroll
    for (int o = 16; o > 0; o >>= 1) {
        s += __shfl_xor_sync(0xffffffffu, s, o);
        q += __shfl_xor_sync(0xffffffffu, q, o);
    }
    return make_float2(sh + s * (1.f / 112), q - s * s * (1.f / 112));
}
__device__ __forceinline__ void ln_final(const float2* stat, float& mean, float& rsd) {
    const float4 a = *(const float4*)stat, b = *(const float4*)(stat + 2);
    const float m = ((a.x + a.z) + (b.x + b.z)) * 0.25f;
    const float e0 = a.x - m, e1 = a.z - m, e2 = b.x - m, e3 = b.z - m;
    const float m2 = ((a.y + a.w) + (b.y + b.w)) + 112.f * ((e0 * e0 + e1 * e1) + (e2 * e2 + e3 * e3));
    float sd;
    asm("sqrt.approx.ftz.f32 %0, %1;" : "=f"(sd) : "f"(bfr(bfr(fmaxf(m2 * (1.f / DM), 0.f)) + 1e-5f)));
    mean = bfr(m);
    rsd = rcp(bfr(sd));
}
template <int MT, bool FOLD>
__device__ __forceinline__ void ln_gemv(const uint32_t (*af)[MT][4], uint2 xp, float2* part, float2* stat, int tid) {
    const int lane = tid & 31, w = tid >> 5;
    if (!FOLD) {
        const float2 st = ln_partial(xp, lane);
        if (lane == 0) stat[w] = st;
        bar_c();
        float mean, rsd;
        ln_final(stat, mean, rsd);
        xp.x = pack_bf(bfr(bf_lo(xp.x) - mean) * rsd, bfr(bf_hi(xp.x) - mean) * rsd);
        xp.y = pack_bf(bfr(bf_lo(xp.y) - mean) * rsd, bfr(bf_hi(xp.y) - mean) * rsd);
    }
    float c[2][MT][4];
#pragma unroll
    for (int i = 0; i < 2 * MT * 4; i++) (&c[0][0][0])[i] = 0.f;
    const bool ones = FOLD && (lane & 4);
#pragma unroll
    for (int k = 0; k < 7; k++) {
        uint32_t b0 = __shfl_sync(0xffffffffu, xp.x, k * 4 + (lane & 3));
        uint32_t b1 = __shfl_sync(0xffffffffu, xp.y, k * 4 + (lane & 3));
        if (ones) b0 = b1 = 0x3f803f80u;
#pragma unroll
        for (int m = 0; m < MT; m++) mma16816(c[k & 1][m], af[k][m], b0, b1);
    }
    float2 st;
    if (FOLD) st = ln_partial(xp, lane);
    if ((lane & 3) == 0) {
#pragma unroll
        for (int m = 0; m < MT; m++)
            *(float4*)(part + w * (16 * MT) + (lane >> 2) * (2 * MT) + 2 * m) =
                make_float4(c[0][m][0] + c[1][m][0], c[0][m][1] + c[1][m][1], c[0][m][2] + c[1][m][2], c[0][m][3] + c[1][m][3]);
        if (FOLD && lane == 0) stat[w] = st;
    }
    bar_c();
}
template <int MT, bool FOLD>
__device__ __forceinline__ float2 ln_cols(const float2* part, int col, float mean, float rsd) {
    const float4 a = *(const float4*)(part + col), b = *(const float4*)(part + 16 * MT + col);
    const float4 c = *(const float4*)(part + 32 * MT + col), d = *(const float4*)(part + 48 * MT + col);
    if (!FOLD) return make_float2((a.x + b.x) + (c.x + d.x), (a.z + b.z) + (c.z + d.z));
    return make_float2((((a.x + b.x) + (c.x + d.x)) - mean * ((a.y + b.y) + (c.y + d.y))) * rsd,
                       (((a.z + b.z) + (c.z + d.z)) - mean * ((a.w + b.w) + (c.w + d.w))) * rsd);
}
__device__ __forceinline__ uint32_t pk_lo(uint32_t a, uint32_t b) { return __byte_perm(a, b, 0x5410); }
__device__ __forceinline__ uint32_t pk_hi(uint32_t a, uint32_t b) { return __byte_perm(a, b, 0x7632); }

__device__ __forceinline__ void frag16(uint32_t (*a)[4], const uint4* wr) {
#pragma unroll
    for (int m = 0; m < 8; m++) {
        const uint32_t r0 = (&wr[0 + (m >> 2)].x)[m & 3], r1 = (&wr[2 + (m >> 2)].x)[m & 3];
        const uint32_t r2 = (&wr[4 + (m >> 2)].x)[m & 3], r3 = (&wr[6 + (m >> 2)].x)[m & 3];
        a[m][0] = pk_lo(r0, r1);
        a[m][1] = pk_hi(r0, r1);
        a[m][2] = pk_lo(r2, r3);
        a[m][3] = pk_hi(r2, r3);
#pragma unroll
        for (int i = 0; i < 4; i++) asm volatile("" : "+r"(a[m][i]));
    }
}
__device__ __forceinline__ void gemv16(float* acc, const uint32_t (*a)[4], uint32_t b0, uint32_t b1, int lane) {
    float y[8][4];
#pragma unroll
    for (int m = 0; m < 8; m++) {
        y[m][0] = y[m][1] = y[m][2] = y[m][3] = 0.f;
        mma16816(y[m], a[m], b0, b1);
    }
    const bool t1 = lane & 1, t2 = lane & 2;
#pragma unroll
    for (int i = 0; i < 4; i++) {
        const int m = i >> 1, e = (i & 1) * 2;
        acc[i] += t2 ? (t1 ? y[6 + m][e] : y[4 + m][e]) : (t1 ? y[2 + m][e] : y[m][e]);
    }
}

__device__ __forceinline__ uint2 mb_poll(int cta, int tid, uint32_t tag) {
    const uint4* p = g_mb + cta * 112 + (tid >> 5) * 28 + min(tid & 31, 27);
    int it = 0;
    while (true) {
        const uint4 a = ld_pkt(p);
        if (__all_sync(0xffffffffu, a.z == tag)) return make_uint2(a.x, a.y);
        if (++it > SPIN_MAX) __trap();
    }
}

__device__ __forceinline__ float gelu_tanh(float x) {
    const float u = (-2.f * 0.7978845608028654f * 1.4426950408889634f) * (x + 0.044715f * x * x * x);
    return __fdividef(x, 1.f + ex2(fminf(u, 120.f)));
}

template <bool PRE>
__device__ __forceinline__ void tile_step(St& s, bool sg, const uint32_t (*kf)[4], uint32_t (*a)[4], uint32_t va, uint32_t scw,
                                          uint32_t scr, uint32_t lb, uint32_t ebar) {
    const float SC = 0.0625f * 1.4426950408889634f;
    float c[4][4];
#pragma unroll
    for (int i = 0; i < 4; i++) c[i][0] = c[i][1] = c[i][2] = c[i][3] = 0.f;
    if (PRE) {
#pragma unroll
        for (int i = 0; i < 8; i++) mma16816(c[i & 1], kf[i], s.q[i & 6], s.q[(i & 6) + 1]);
    } else {
#pragma unroll
        for (int i = 0; i < 4; i++) mma16816(c[i], kf[i], s.q[i & 6], s.q[(i & 6) + 1]);
#pragma unroll
        for (int i = 0; i < 4; i++) ldsm4t(a[i], va ^ (i * 32));
#pragma unroll
        for (int i = 4; i < 8; i++) mma16816(c[i & 3], kf[i], s.q[i & 6], s.q[(i & 6) + 1]);
#pragma unroll
        for (int i = 4; i < 8; i++) ldsm4t(a[i], (va ^ ((i & 3) * 32)) + 8192);
    }
    const bool mine = ((lb & 2) != 0) == sg;
    {
        const bool t1 = lb & 1;
        float v[4];
#pragma unroll
        for (int i = 0; i < 4; i++) v[i] = PRE ? (t1 ? c[1][i] : c[0][i]) : (t1 ? c[1][i] + c[3][i] : c[0][i] + c[2][i]);
        asm volatile("{\n.reg .pred p;\nsetp.ne.u32 p, %5, 0;\n@p st.shared.f32 [%0], %1;\n@p st.shared.f32 [%0+128], %2;\n"
                     "@p st.shared.f32 [%0+32], %3;\n@p st.shared.f32 [%0+160], %4;\n}" ::"r"(scw),
                     "f"(v[0]), "f"(v[1]), "f"(v[2]), "f"(v[3]), "r"((uint32_t)mine) : "memory");
    }
    bar_c();
    float2 p0, p1, p2, p3;
    asm volatile("ld.shared.v2.f32 {%0,%1}, [%2];" : "=f"(p0.x), "=f"(p0.y) : "r"(scr) : "memory");
    asm volatile("ld.shared.v2.f32 {%0,%1}, [%2+512];" : "=f"(p1.x), "=f"(p1.y) : "r"(scr) : "memory");
    asm volatile("ld.shared.v2.f32 {%0,%1}, [%2+1024];" : "=f"(p2.x), "=f"(p2.y) : "r"(scr) : "memory");
    asm volatile("ld.shared.v2.f32 {%0,%1}, [%2+1536];" : "=f"(p3.x), "=f"(p3.y) : "r"(scr) : "memory");
    if (!PRE && (lb & 64)) mbar_arrive(ebar);
    float m = sg ? s.m1 : s.m0, l = sg ? s.l1 : s.l0;
    const float s0 = bfr((p0.x + p1.x) + (p2.x + p3.x)) * SC;
    const float s1 = bfr((p0.y + p1.y) + (p2.y + p3.y)) * SC;
    float mx = fmaxf(s0, s1);
    if (__any_sync(0xffffffffu, mx > m)) {
        {
            int k = __float_as_int(mx);
            k ^= (k >> 31) & 0x7fffffff;
            const bool hi = lb & 32;
            const int k0 = __reduce_max_sync(0xffffffffu, hi ? INT_MIN : k);
            const int k1 = __reduce_max_sync(0xffffffffu, hi ? k : INT_MIN);
            k = hi ? k1 : k0;
            k ^= (k >> 31) & 0x7fffffff;
            mx = __int_as_float(k);
        }
        const float mn = fmaxf(mx, m);
        const float al = (mn == -INFINITY) ? 1.f : ex2(m - mn);
        float f0 = __shfl_sync(0xffffffffu, al, 0), f1 = __shfl_sync(0xffffffffu, al, 16);
        if (!mine) f0 = f1 = 1.f;
        l *= al;
        m = mn;
        if (sg) s.m1 = m; else s.m0 = m;
#pragma unroll
        for (int i = 0; i < 4; i++) {
            s.acc[4 * i + 0] *= f0; s.acc[4 * i + 1] *= f1;
            s.acc[4 * i + 2] *= f0; s.acc[4 * i + 3] *= f1;
        }
    }
    const uint32_t pk = pack_bf(ex2(s0 - m), ex2(s1 - m));
    uint32_t b[4];
    const bool col = ((lb & 32) != 0) == sg;
#pragma unroll
    for (int i = 0; i < 4; i++) {
        b[i] = __shfl_sync(0xffffffffu, pk, (lb & 31) + 4 * i);
        if (!col) b[i] = 0;
    }
    l += bf_lo(pk) + bf_hi(pk);
    if (sg) s.l1 = l; else s.l0 = l;
#pragma unroll
    for (int i = 0; i < 8; i++) mma16816(s.acc + 4 * (i & 3), a[i], b[(i >> 2) * 2], b[(i >> 2) * 2 + 1]);
}

__global__ void __launch_bounds__(512, 1)
fused_kernel(const __grid_constant__ CUtensorMap tmK, const __grid_constant__ CUtensorMap tmV,
             const __grid_constant__ CUtensorMap tmKs, const __grid_constant__ CUtensorMap tmVs,
             const __grid_constant__ CUtensorMap tmQ, const Params P) {
    extern __shared__ __align__(1024) unsigned char smem[];
    const int tid = threadIdx.x;
    const int cta = blockIdx.x;
    const int G = gridDim.x;
    const uint32_t sb = smem_u32(smem);
    volatile int* meta = (volatile int*)(smem + OFF_META);
    volatile int* hslot = (volatile int*)(smem + OFF_HSLOT);

    const int warp = __shfl_sync(0xffffffffu, tid >> 5, 0);
    if (warp >= 4 && warp < 12) {
        asm volatile("bar.sync 0, 512;" ::: "memory");
        asm volatile("setmaxnreg.inc.sync.aligned.u32 %0;" ::"n"(REG_H));
        const uint32_t so = sb + (tid - 128) * 16;
        uint4 r[NA * 8];
#pragma unroll
        for (int i = 0; i < NA; i++) {
            mbar_wait(sb + OFF_HREQ + i * 8, 0);
            uint32_t hs;
            asm volatile("ld.shared.u32 %0, [%1];" : "=r"(hs) : "r"(sb + OFF_HSLOT + i * 4) : "memory");
            mbar_wait(sb + OFF_FULL + (hs & ~7u), hs & 1);
            const uint32_t d = so + (hs & ~7u) * (SLOT / 8);
#pragma unroll
            for (int k = 0; k < 8; k++) {
                uint4& v = r[i * 8 + k];
                asm volatile("ld.shared.v4.u32 {%0,%1,%2,%3}, [%4];" : "=r"(v.x), "=r"(v.y), "=r"(v.z), "=r"(v.w) : "r"(d + k * 4096) : "memory");
            }
            asm volatile("bar.sync 2, 256;" ::: "memory");
            if (so == sb) mbar_arrive(sb + OFF_EMPTY + (hs & ~7u));
        }
#pragma unroll
        for (int i = 0; i < NA; i++) {
            mbar_wait(sb + OFF_HREQ + i * 8, 1);
            uint32_t hs;
            asm volatile("ld.shared.u32 %0, [%1];" : "=r"(hs) : "r"(sb + OFF_HSLOT + i * 4) : "memory");
            const uint32_t d = so + (hs & ~7u) * (SLOT / 8);
#pragma unroll
            for (int k = 0; k < 8; k++) {
                const uint4 v = r[i * 8 + k];
                asm volatile("st.shared.v4.u32 [%0], {%1,%2,%3,%4};" ::"r"(d + k * 4096), "r"(v.x), "r"(v.y), "r"(v.z), "r"(v.w) : "memory");
            }
            asm volatile("fence.proxy.async.shared::cta;" ::: "memory");
            asm volatile("bar.sync 2, 256;" ::: "memory");
            if (so == sb) mbar_arrive(sb + OFF_FULL + (hs & ~7u));
        }
    } else if (warp < 4) {
        asm volatile("setmaxnreg.dec.sync.aligned.u32 %0;" ::"n"(REG_C));
        float* sc = (float*)(smem + OFF_SC);
        float* red = (float*)(smem + OFF_RED);
        volatile uint2* xown = (volatile uint2*)(smem + OFF_XO);
        uint32_t tagp;
        asm volatile("ld.relaxed.gpu.global.u32 %0, [%1];" : "=r"(tagp) : "l"(&g_epoch) : "memory");
        uint32_t rs = 2;

#pragma unroll 1
        while (true) {
            const bool first = rs & 2;
            if (cta < 128) {
                const int tid = tid_now();
                const int lane = tid & 31, w = tid >> 5;
                uint2 xp = make_uint2(0, 0);
                uint2 wr[28];
                if (first) {
                    xp = ldg64(P.x + (w * 28 + min(lane, 27)) * 4);
                    asm volatile("bar.sync 0, 512;" ::: "memory");
                    mbar_wait(sb + OFF_JB + 24, 0);
                    const unsigned char* p = smem + (NS - 1) * SLOT + (w * 112 + (lane & 3) * 4) * 64 + (lane >> 2) * 8;
#pragma unroll
                    for (int r = 0; r < 28; r++) wr[r] = *(const uint2*)(p + ((r >> 2) * 16 + (r & 3)) * 64);
                } else {
                    const uint64_t pol = pol_first();
                    const __nv_bfloat16* p = P.wq + (size_t)(w * 112 + (lane & 3) * 4) * NQ + ((cta + 64) & 127) * 32 + (lane >> 2) * 4;
#pragma unroll
                    for (int r = 0; r < 28; r++) wr[r] = ldg64p(p + (size_t)((r >> 2) * 16 + (r & 3)) * NQ, pol);
                }
                uint32_t af[7][2][4];
#pragma unroll
                for (int k = 0; k < 7; k++) {
                    af[k][0][0] = pk_lo(wr[4 * k].x, wr[4 * k + 1].x);
                    af[k][0][1] = pk_hi(wr[4 * k].x, wr[4 * k + 1].x);
                    af[k][0][2] = pk_lo(wr[4 * k + 2].x, wr[4 * k + 3].x);
                    af[k][0][3] = pk_hi(wr[4 * k + 2].x, wr[4 * k + 3].x);
                    af[k][1][0] = pk_lo(wr[4 * k].y, wr[4 * k + 1].y);
                    af[k][1][1] = pk_hi(wr[4 * k].y, wr[4 * k + 1].y);
                    af[k][1][2] = pk_lo(wr[4 * k + 2].y, wr[4 * k + 3].y);
                    af[k][1][3] = pk_hi(wr[4 * k + 2].y, wr[4 * k + 3].y);
#pragma unroll
                    for (int i = 0; i < 8; i++) asm volatile("" : "+r"((&af[k][0][0])[i]));
                }
                uint4* pq = g_q + ((cta + 64) & 127) * 8 + (tid & 7);
                asm volatile("" : "+l"(pq));
                if (first) {
                    tagp = (tagp + 1) << 5;
                } else {
                    xp = mb_poll(cta, tid, tagp | 11);
                    tagp |= 16;
                }
                ln_gemv<2, FOLD_Q>(af, xp, (float2*)sc, (float2*)red, tid);
                if (tid < 8) {
                    float mean = 0.f, rsd = 0.f;
                    if (FOLD_Q) ln_final((const float2*)red, mean, rsd);
                    const int c0 = (tid >> 2) * 16 + (tid & 3) * 2;
                    const float2 v0 = ln_cols<2, FOLD_Q>((const float2*)sc, c0, mean, rsd);
                    const float2 v1 = ln_cols<2, FOLD_Q>((const float2*)sc, c0 + 8, mean, rsd);
                    st_pkt(pq, pack_bf(v0.x, v0.y), pack_bf(v1.x, v1.y), tagp | 15, tagp | 15);
                }
                bar_c();
            } else {
                if (first) {
                    asm volatile("bar.sync 0, 512;" ::: "memory");
                    mbar_wait(sb + OFF_JB + 24, 0);
                    bar_c();
                }
                tagp = first ? (tagp + 1) << 5 : tagp | 16;
            }
            rs &= ~2u;

            St st;
#pragma unroll
            for (int i = 0; i < 16; i++) st.acc[i] = 0.f;
            st.m0 = st.m1 = -INFINITY;
            st.l0 = st.l1 = 0.f;
            uint32_t lds_k, lds_v, scw, scr, src;
            {
                const int t = tid_now();
                const int lane = t & 31, w = t >> 5;
                lds_k = sb + w * 1024 + ((lane >> 3) & 1) * 4096 + (lane & 7) * 128 + (((lane >> 4) ^ (lane & 7)) << 4);
                lds_v = sb + 16384 + w * 1024 + (lane >> 4) * 4096 + (lane & 7) * 128 + ((((lane >> 3) & 1) ^ (lane & 7)) << 4);
                scw = sb + OFF_SC + w * 512 + ((lane & 1) * 16 + (lane >> 2)) * 4;
                scr = sb + OFF_SC + lane * 8;
                src = ((lane >> 2) & 1) * 16 + (lane & 3) + (lane >> 4) * 32 + (t == 0 ? 64 : 0);
                asm volatile("" : "+r"(lds_k), "+r"(lds_v), "+r"(scw), "+r"(scr), "+r"(src));
            }
            if (first && (src & 64)) mbar_arrive(sb + OFF_HREQ + 56);
            mbar_wait(sb + OFF_FULL + (rs & ~7u), rs & 1);
            const int mt0 = meta[rs >> 3];
            if (!(mt0 & M_SVC)) {
                const uint32_t tb = (rs & ~7u) * (SLOT / 8);
                uint32_t kf[8][4], vf[8][4];
#pragma unroll
                for (int i = 0; i < 8; i++) ldsm4(kf[i], ((lds_k + tb) ^ ((i >> 1) * 32)) + (i & 1) * 8192);
#pragma unroll
                for (int i = 0; i < 8; i++) ldsm4t(vf[i], ((lds_v + tb) ^ ((i & 3) * 32)) + (i >> 2) * 8192);
                bar_c();
                if (src & 64) mbar_arrive(sb + OFF_EMPTY + (rs & ~7u));
                __syncwarp();
                st_loadq(st, 0, 7, tagp | 15);
                tile_step<true>(st, (mt0 & M_USE1) != 0, kf, vf, 0, scw, scr, src, 0);
                scw ^= 256;
                scr ^= 256;
                rs += 8;
                if ((rs >> 3) == NS) rs = (rs & 1) ^ 1;
            } else {
                st_loadq(st, 0, 7, tagp | 15);
            }
            int bk = 0;

#pragma unroll 1
            while (true) {
                mbar_wait(sb + OFF_FULL + (rs & ~7u), rs & 1);
                int mt = meta[rs >> 3];
                const uint32_t tb = (rs & ~7u) * (SLOT / 8);
                uint32_t kf[8][4];
#pragma unroll
                for (int i = 0; i < 8; i++) ldsm4(kf[i], ((lds_k + tb) ^ ((i >> 1) * 32)) + (i & 1) * 8192);
                mt &= ~(bk >> 2) | ~M_SVC;
                if (mt & M_SVC) {
                    if ((mt & M_END) && (bk & 0x3ff) == (mt >> 16)) break;
                    asm volatile("" : "+r"(tagp));
                    const int pass = (tagp >> 4) & 1;
                    const int head = mt & 15;
                    if (pass && !(bk & 512) && (head >= 6 || (mt & M_SW))) {
                        st_flush(st, 1, 2, cta, tagp | 7);
                        bk |= 512;
                        if (head >= 6) st_loadq(st, bk & 7, 6, tagp | 15);
                    }
                    if (!(mt & (M_SIDE | M_NOP))) {
                        const bool adv = head != (bk & 15) || (mt & M_END);
#pragma unroll 1
                        while (true) {
                            const int cur = bk & 15, ncomb = (bk >> 4) & 15;
                            int ch;
                            if (ncomb == cur && cur < head) {
                                st_flush(st, 0, cur & 1, cta, tagp | cur);
                                bk++;
                                if (cur + 1 == head && !(mt & M_END)) break;
                                continue;
                            }
                            if (pass && !(bk & 256) && ncomb == cur && ((mt & M_END) || (!adv && cur >= 2))) ch = 7;
                            else if (ncomb < cur) ch = ncomb;
                            else break;
                            const bool s7 = pass && ch == 7;
                            float on[4];
                            const bool ok = combine(adv, on, s7 ? 2 : (ch & 1), G, cta, tagp | ch, red + (bk & 1024 ? 32 : 0));
                            if (ok) *(float4*)(red + 96 + ch * 4) = make_float4(on[0], on[1], on[2], on[3]);
                            bk ^= 1024;
                            if (ok) bk += s7 ? 256 : 16;
                            if (!adv) break;
                        }
                        if (adv && !(mt & (M_USE1 | M_END))) st_loadq(st, head, (bk & 512) ? 6 : 7, tagp | 15);
                    }
                    if (mt & (M_NOP | M_END)) {
                        if (mt & M_END) break;
                        bar_c();
                        if (src & 64) mbar_arrive(sb + OFF_EMPTY + (rs & ~7u));
                        rs += 8;
                        if ((rs >> 3) == NS) rs = (rs & 1) ^ 1;
                        continue;
                    }
                    meta[7] = ((bk >> 4) & 15) < (bk & 15) || (pass && !(bk & 256) && (bk & 15) >= 2);
                    bk |= 2048;
                    continue;
                }
                bk &= ~2048;
                const uint32_t ebar = sb + OFF_EMPTY + (rs & ~7u);
                uint32_t vf[8][4];
                tile_step<false>(st, (mt & M_USE1) != 0, kf, vf, lds_v + tb, scw, scr, src, ebar);
                scw ^= 256;
                scr ^= 256;
                rs += 8;
                if ((rs >> 3) == NS) rs = (rs & 1) ^ 1;
            }
            asm volatile("" : "+r"(tagp));
            const int pass = (tagp >> 4) & 1;
            const int tid = tid_now();
            const int lane = tid & 31, w = tid >> 5;
            float xacc[4] = {0.f, 0.f, 0.f, 0.f};
            mbar_wait(sb + OFF_JB + 8, pass);
            st_flush(st, pass, pass ^ 1, cta, tagp | (7 - pass));
            {
                uint4* pm = g_ma + ((tid >> 3) * 128 + cta) * 8 + (tid & 7);
                asm volatile("" : "+l"(pm));
                if (cta < 128) {
                    uint2 wr[32];
                    {
                        const int row0 = ((cta >> 1) & 1) * 256 + (cta >> 5) * 64 + ((cta >> 2) & 7) + (cta & 1) * 8;
                        const __nv_bfloat16* wp = P.wo + (size_t)row0 * DM + (tid < 112 ? tid : 0) * 4;
                        const uint64_t pol = pol_first();
#pragma unroll
                        for (int i = 0; i < 24; i++) wr[i] = ldg64p(wp + ((i >> 2) * 512 + (i & 3) * 16) * DM, pol);
#pragma unroll
                        for (int i = 0; i < 4; i++) wr[24 + i] = ldg64p(wp + ((6 + pass) * 512 + i * 16) * DM, pol);
#pragma unroll
                        for (int i = 0; i < 4; i++) wr[28 + i] = ldg64p(wp + ((7 - pass) * 512 + i * 16) * DM, pol);
                    }
#pragma unroll
                    for (int i = 0; i < 28; i++) {
                        const float o = red[96 + (i < 24 ? i : i + pass * 4)];
                        xacc[0] += o * bf_lo(wr[i].x);
                        xacc[1] += o * bf_hi(wr[i].x);
                        xacc[2] += o * bf_lo(wr[i].y);
                        xacc[3] += o * bf_hi(wr[i].y);
                    }
#pragma unroll
                    for (int i = 0; i < 4; i++) asm volatile("" : "+f"(xacc[i]));
                    float on[4];
                    combine(true, on, pass ^ 1, G, cta, tagp | (7 - pass), red + 64);
#pragma unroll
                    for (int i = 0; i < 4; i++) {
                        xacc[0] += on[i] * bf_lo(wr[28 + i].x);
                        xacc[1] += on[i] * bf_hi(wr[28 + i].x);
                        xacc[2] += on[i] * bf_lo(wr[28 + i].y);
                        xacc[3] += on[i] * bf_hi(wr[28 + i].y);
                    }
                }
                if (tid < 112 && cta < 128) st_pkt4(pm, xacc, tagp | 8);
            }
            if (cta >= 128) bar_c();
            if (tid == 127) {
                mbar_arrive(sb + OFF_EMPTY + (rs & ~7u));
            }
            rs += 8;
            if ((rs >> 3) == NS) rs = (rs & 1) ^ 1;
            __syncwarp();
            const int own = G - 1 - cta;
            if (own < 14) {
#pragma unroll 1
                for (int stage = 0; stage < 2; stage++) {
                    const uint32_t tg = tagp | (8 + 2 * stage);
                    const uint4* p = g_ma + own * 1024 + tid;
                    uint4 a[8];
                    int it = 0;
                    while (true) {
#pragma unroll
                        for (int k = 0; k < 7; k++) a[k] = ld_pkt(p + k * 128);
                        a[7] = ld_pkt(p + (stage ? 0 : 7 * 128));
                        uint32_t bad = 0;
#pragma unroll
                        for (int k = 0; k < 8; k++) bad |= a[k].x ^ tg;
                        if (__all_sync(0xffffffffu, (bad & 255) == 0)) break;
                        if (++it > SPIN_MAX) __trap();
                    }
                    if (stage) a[7] = make_uint4(0, 0, 0, 0);
                    float v[4];
#define SUM8(c) (((__uint_as_float(a[0].c) + __uint_as_float(a[1].c)) + (__uint_as_float(a[2].c) + __uint_as_float(a[3].c))) + \
                 ((__uint_as_float(a[4].c) + __uint_as_float(a[5].c)) + (__uint_as_float(a[6].c) + __uint_as_float(a[7].c))))
                    v[0] = SUM8(x); v[1] = SUM8(y); v[2] = SUM8(z); v[3] = SUM8(w);
#undef SUM8
                    {
                        const bool up = lane & 16;
                        v[0] = (up ? v[2] : v[0]) + __shfl_xor_sync(0xffffffffu, up ? v[0] : v[2], 16);
                        v[1] = (up ? v[3] : v[1]) + __shfl_xor_sync(0xffffffffu, up ? v[1] : v[3], 16);
                    }
                    {
                        const bool up = lane & 8;
                        v[0] = (up ? v[1] : v[0]) + __shfl_xor_sync(0xffffffffu, up ? v[0] : v[1], 8);
                    }
                    float* rb = sc + stage * 128;
                    rb[w * 32 + (lane & 7) * 4 + (lane >> 4) * 2 + ((lane >> 3) & 1)] = v[0];
                    const uint32_t xo0 = xown[tid & 7].x, xo1 = xown[tid & 7].y;
                    const uint32_t b20 = stage ? xown[8 + (tid & 7)].x : 0u, b21 = stage ? xown[8 + (tid & 7)].y : 0u;
                    bar_c();
                    uint2 xn;
                    {
                        const float* rp = rb + (tid & 7) * 4;
                        const float4 r0 = *(const float4*)(rp), r1 = *(const float4*)(rp + 32);
                        const float4 r2 = *(const float4*)(rp + 64), r3 = *(const float4*)(rp + 96);
                        float t0 = bfr((r0.x + r1.x) + (r2.x + r3.x)), t1 = bfr((r0.y + r1.y) + (r2.y + r3.y));
                        float t2 = bfr((r0.z + r1.z) + (r2.z + r3.z)), t3 = bfr((r0.w + r1.w) + (r2.w + r3.w));
                        xn.x = pack_bf(bf_lo(xo0) + bfr(t0 + bf_lo(b20)), bf_hi(xo0) + bfr(t1 + bf_hi(b20)));
                        xn.y = pack_bf(bf_lo(xo1) + bfr(t2 + bf_lo(b21)), bf_hi(xo1) + bfr(t3 + bf_hi(b21)));
                    }
                    if (stage && pass) {
                        if (tid < 8) *(uint2*)(P.out + own * 32 + tid * 4) = xn;
                        break;
                    }
                    uint4* pp = g_mb + (tid >> 3) * 112 + own * 8 + (tid & 7);
#pragma unroll
                    for (int k = 0; k < 7; k++) st_pkt(pp + ((k + 3) % 7) * 16 * 112, xn.x, xn.y, tg | 1, tg | 1);
                    if (stage) st_pkt(pp + 7 * 16 * 112, xn.x, xn.y, tg | 1, tg | 1);
                    if (tid < 8) { xown[tid].x = xn.x; xown[tid].y = xn.y; }
                    if (tid == 0 && own == 0 && !stage) {
                        if (pass) { g_ctr1[0] = 0; g_epoch = tagp >> 5; }
                        else g_ctr0[0] = 0;
                    }
                    bar_c();
                }
            } else if (cta < 112) {
                uint32_t a1[7][1][4], a2[8][4];
                {
                    const uint64_t pol = pol_first();
                    uint32_t w1r[28];
                    uint4 w2r[8];
                    const __nv_bfloat16* p1 = P.w1 + (size_t)(w * 112 + (lane & 3) * 4) * FF + cta * 16 + (lane >> 2) * 2;
#pragma unroll
                    for (int r = 0; r < 28; r++) w1r[r] = ldg32p(p1 + (size_t)((r >> 2) * 16 + (r & 3)) * FF, pol);
                    const __nv_bfloat16* p2 = P.w2 + (size_t)(cta * 16 + (lane & 3) * 4) * DM + w * 112 + min(lane >> 2, 6) * 8;
#pragma unroll
                    for (int r = 0; r < 8; r++) w2r[r] = ldg128(p2 + (r >> 1) * DM + (r & 1) * 56, pol);
#pragma unroll
                    for (int k = 0; k < 7; k++) {
                        a1[k][0][0] = pk_lo(w1r[4 * k], w1r[4 * k + 1]);
                        a1[k][0][1] = pk_hi(w1r[4 * k], w1r[4 * k + 1]);
                        a1[k][0][2] = pk_lo(w1r[4 * k + 2], w1r[4 * k + 3]);
                        a1[k][0][3] = pk_hi(w1r[4 * k + 2], w1r[4 * k + 3]);
#pragma unroll
                        for (int i = 0; i < 4; i++) asm volatile("" : "+r"(a1[k][0][i]));
                    }
                    frag16(a2, w2r);
                }
                const int pk = w * 28 + (lane >> 2) * 2 + (lane & 1) + (lane & 2) * 7;
                uint4* pm = g_ma + ((pk >> 3) * 128 + cta) * 8 + (pk & 7);
                asm volatile("" : "+l"(pm));
                const uint2 xp = mb_poll(cta, tid, tagp | 9);
                ln_gemv<1, FOLD_M>(a1, xp, (float2*)sc, (float2*)red, tid);
                float mean = 0.f, rsd = 0.f;
                if (FOLD_M) ln_final((const float2*)red, mean, rsd);
                const float2 h0 = ln_cols<1, FOLD_M>((const float2*)sc, (lane & 3) * 4, mean, rsd);
                const float2 h1 = ln_cols<1, FOLD_M>((const float2*)sc, (lane & 3) * 4 + 2, mean, rsd);
                const uint2 bb = *(const uint2*)(smem + OFF_XO + (lane & 3) * 8);
                const uint32_t g0 = pack_bf(gelu_tanh(bfr(bfr(h0.x) + bf_lo(bb.x))), gelu_tanh(bfr(bfr(h0.y) + bf_hi(bb.x))));
                const uint32_t g1 = pack_bf(gelu_tanh(bfr(bfr(h1.x) + bf_lo(bb.y))), gelu_tanh(bfr(bfr(h1.y) + bf_hi(bb.y))));
                xacc[0] = xacc[1] = xacc[2] = xacc[3] = 0.f;
                gemv16(xacc, a2, g0, g1, lane);
                if (lane < 28) st_pkt4(pm, xacc, tagp | 10);
                bar_c();
            }
            if (tagp & 16) break;
        }
    } else {
        asm volatile("setmaxnreg.dec.sync.aligned.u32 %0;" ::"n"(REG_P));
        if (tid == 384) {
            if (sb & 1023) __trap();
#pragma unroll
            for (int i = 0; i < NS; i++) mbar_init(sb + OFF_FULL + i * 8, 1);
            mbar_init(sb + OFF_JB + 24, 1);
            asm volatile("fence.proxy.async.shared::cta;" ::: "memory");
#pragma unroll
            for (int i = 0; i < 2; i++) {
                if (i == 0) {
                    mbar_expect(sb + OFF_JB + 24, DM * 64);
                    tma2(sb + (NS - 1) * SLOT, &tmQ, ((cta + 64) & 127) * 32, 0, sb + OFF_JB + 24);
                    tma2(sb + (NS - 1) * SLOT + 224 * 64, &tmQ, ((cta + 64) & 127) * 32, 224, sb + OFF_JB + 24);
                }
                mbar_expect(sb + OFF_FULL + i * 8, SLOT);
                tma4(sb + i * SLOT, &tmK, (cta + i * G) * 4, sb + OFF_FULL + i * 8, pol_first());
                tma4(sb + i * SLOT + 16384, &tmV, (cta + i * G) * 4, sb + OFF_FULL + i * 8, pol_first());
            }
#pragma unroll
            for (int i = 0; i < NS; i++) {
                mbar_init(sb + OFF_EMPTY + i * 8, 2);
                meta[i] = 0;
            }
            meta[7] = 0;
#pragma unroll
            for (int i = 0; i < 8; i++) mbar_init(sb + OFF_HREQ + i * 8, 1);
#pragma unroll
            for (int i = 0; i < 3; i++) mbar_init(sb + OFF_JB + i * 8, 1);
        }
        __syncwarp();
        if (warp == 12) asm volatile("bar.arrive 0, 512;" ::: "memory");
        else asm volatile("bar.sync 0, 512;" ::: "memory");
        if (warp == 13) {
            const int lane = tid - 416;
            if (lane < 16) {
                const int own = G - 1 - cta;
                const __nv_bfloat16* p = own < 14 ? (lane < 8 ? P.x : P.b2) + own * 32 + (lane & 7) * 4
                                                  : P.b1 + (cta < 112 ? cta : 0) * 16 + (lane & 3) * 4;
                *(uint2*)(smem + OFF_XO + lane * 8) = ldg64(p);
            }
#pragma unroll 1
            for (int pass = 0; pass < 2; pass++) {
                mbar_wait(sb + OFF_JB, pass);
                int cta;
                asm volatile("mov.u32 %0, %ctaid.x;" : "=r"(cta));
                if (G - 1 - cta < 14) {
#pragma unroll 1
                    for (int i = lane; i < 1024; i += 32) st_pkt(g_ma + (G - 1 - cta) * 1024 + i, 0, 0, 0, 0);
                }
                if (cta < 128) {
#pragma unroll 1
                    for (int i = lane; i < 112; i += 32) st_pkt(g_mb + cta * 112 + i, 0, 0, 0, 0);
                }
                __threadfence();
                __syncwarp();
                if (lane == 0) mbar_arrive(sb + OFF_JB + 8);
                {
                    const int row = ((cta >> 1) & 1) * 256 + ((cta >> 5) & 3) * 64 + ((cta >> 2) & 7) + (cta & 1) * 8 + (lane >> 2) * 512 + (lane & 3) * 16;
                    const char* wp = (const char*)(P.wo + (size_t)row * DM);
                    mbar_wait(sb + OFF_JB + 16, pass);
                    if (cta < 128) l2_prefetch(wp, DM * 2);
                }
                __syncwarp();
                if (lane == 0) {
                    asm volatile("mov.u32 %0, %ctaid.x;" : "=r"(cta));
                    if (cta < 128) {
                        {
                            const uint32_t t = timer_lo() + PF_DELAY_W;
                            while ((int)(timer_lo() - t) < 0) {}
                        }
                        l2_prefetch((const char*)P.w1 + cta * (DM * FF * 2 / 128), DM * FF * 2 / 128);
                        l2_prefetch((const char*)P.w2 + cta * (DM * FF * 2 / 128), DM * FF * 2 / 128);
                        if (!pass) l2_prefetch((const char*)P.wq + cta * (DM * NQ * 2 / 128), DM * NQ * 2 / 128);
                    }
                    if (!pass) {
                        volatile unsigned short* own = (volatile unsigned short*)(smem + OFF_OWN);
                        uint32_t t = timer_lo() + PF_DELAY_T + (cta & 7) * (PF_PACE / 8);
                        int i = 255, k = 0;
#pragma unroll 1
                        while (true) {
                            while ((int)(timer_lo() - t) < 0) {}
                            const int pr = hslot[7];
                            i = min(i, pr >> 8);
                            k = max(k, pr & 255);
                            int tile;
                            if (i > 0 && own[i - 1] >= P.tkeep) tile = own[--i];
                            else if (k < 1) tile = cta + (k++) * G;
                            else break;
                            tma4_prefetch_plain(&tmK, tile * 4);
                            tma4_prefetch_plain(&tmV, tile * 4);
                            t += PF_PACE;
                        }
                    }
                }
                __syncwarp();
            }
        } else if (tid == 384) {
            volatile unsigned short* own = (volatile unsigned short*)(smem + OFF_OWN);
            const int TA0 = P.ta0;
            uint32_t pc = 0, wc = 0, lc = 0;
            int cn = 0;
            auto adv = [&](uint32_t& c) {
                c += 8;
                if ((c >> 3) == NS) c = (c & 1) ^ 1;
            };
            auto acquire = [&](int depth) {
                while ((cn >> 8) >= depth) {
                    mbar_wait(sb + OFF_FULL + (lc & ~7u), lc & 1);
                    adv(lc);
                    cn -= 256;
                }
                if ((cn & 255) == NS) {
                    mbar_wait(sb + OFF_EMPTY + (wc & ~7u), wc & 1);
                    adv(wc);
                    cn--;
                }
            };
            auto post = [&]() {
                adv(pc);
                cn += 257;
            };
            auto load_tile = [&](int tile, bool keep) {
                const uint32_t bar = sb + OFF_FULL + (pc & ~7u);
                const uint32_t dst = sb + (pc & ~7u) * (SLOT / 8);
                mbar_expect(bar, SLOT);
                if (!keep) {
                    tma4(dst, &tmK, tile * 4, bar, pol_first());
                    tma4(dst + 16384, &tmV, tile * 4, bar, pol_first());
                } else {
#pragma unroll
                    for (int o = 0; o < 16384; o += PIECE) {
                        tma4(dst + o, &tmKs, tile * 4 + (o >> 12), bar, pol_first());
                        tma4_prefetch(&tmKs, tile * 4 + (o >> 12), pol_normal());
                    }
#pragma unroll
                    for (int o = 0; o < 16384; o += PIECE) {
                        tma4(dst + 16384 + o, &tmVs, tile * 4 + (o >> 12), bar, pol_first());
                        tma4_prefetch(&tmVs, tile * 4 + (o >> 12), pol_normal());
                    }
                }
            };
            auto mark = [&](int m) {
                meta[pc >> 3] = m;
                mbar_arrive(sb + OFF_EMPTY + (pc & ~7u));
                mbar_arrive(sb + OFF_FULL + (pc & ~7u));
                post();
            };
            int hc = 0;
            auto main_flags = [&](int tile, int last) {
                const int head = tile >> 11;
                int m = head;
                if (head != (hc & 15)) { hc = head; m |= M_SVC; }
                else {
                    hc += 16;
                    if (hc == last + JCNT * 16) mbar_arrive(sb + OFF_JB);
                    if ((((hc >> 4) + cta) & 3) == 3 && hc >= 2 * 16 && meta[7]) m |= M_SVC;
                }
                return m;
            };
            int nxt = (int)ticket(0);
#pragma unroll 1
            for (int i = 0; i < NSTAT; i++) {
                acquire(DEPTH);
                mbar_arrive(sb + OFF_EMPTY + (pc & ~7u));
                if (i >= 2) load_tile(cta + i * G, 0);
                post();
            }
            int na = 0, nown = 0;
#pragma unroll 1
            while (true) {
                acquire(DEPTH);
                if (nxt < 0) nxt = nown < OWNCAP ? (int)ticket(0) : NT;
                if (pc == (NS - 1) * 8) mbar_wait(sb + OFF_HREQ + 56, 0);
                int tile = nxt + NSTAT * G;
                bool isa = false;
                if (tile >= TA0) {
                    isa = na < NA;
                    tile = isa ? TA0 + na * G + cta : tile + G * NA;
                }
                if (tile >= NT) break;
                meta[pc >> 3] = main_flags(tile, 7);
                if (isa) {
                    hslot[na] = pc;
                    mbar_arrive(sb + OFF_HREQ + na * 8);
                    na++;
                    load_tile(tile, false);
                } else {
                    mbar_arrive(sb + OFF_EMPTY + (pc & ~7u));
                    if (tile >= OWN0) own[nown++] = (unsigned short)tile;
                    load_tile(tile, tile >= P.tk0 && tile < P.tkeep);
                    nxt = -1;
                }
                post();
            }
            if ((hc & 15) != 7 || hc < 7 + JCNT * 16) mbar_arrive(sb + OFF_JB);
            mark(M_END | M_SVC | 7 | (0x77 << 16));
            nxt = (int)ticket(1);
            hslot[7] = (nown > NS ? nown - NS : 0) << 8;
            mbar_arrive(sb + OFF_JB + 16);
#pragma unroll 1
            for (int j = 0; j < NS; j++) {
                acquire(NS);
                const int back = j < NS - 1 ? NS - 1 - j : NS;
                mark(nown >= back ? (M_SIDE | M_USE1 | 7) : (M_NOP | M_SVC));
            }
            nown = nown > NS ? nown - NS : 0;
            na = 0;
            hc = 0;
            int np = 0;
#pragma unroll 1
            while (true) {
                const bool side_left = nown > 0 || na < NA;
                acquire(nown > 0 ? DEPTH_MIX : (side_left ? DEPTH + 1 : DEPTH));
                const bool stat = (np & 255) < NSTAT;
                bool side = side_left && !stat &&
                            (nown > 0 ? ((((np >> 8) + cta) & 1) == 0) : ((np >> 16) && (np & 256)));
                int tile = 0;
                if (!side) {
                    if (nxt < 0) nxt = (int)ticket(1);
                    tile = stat ? cta + (np & 255) * G : nxt + NSTAT * G;
                    if (tile >= TA0) tile = NT;
                    side = side_left && tile >= (nown > 0 ? 6 * TPH : NT);
                }
                mbar_arrive(sb + OFF_EMPTY + (pc & ~7u));
                if (side) {
                    if (nown > 0) {
                        meta[pc >> 3] = M_SIDE | M_USE1 | 7;
                        tile = own[--nown];
                        load_tile(tile, false);
                    } else {
                        meta[pc >> 3] = M_SIDE | M_USE1 | 6 | ((na | (np >> 16)) ? 0 : M_SVC);
                        hslot[na] = pc;
                        mbar_arrive(sb + OFF_HREQ + na * 8);
                        na++;
                    }
                } else if (tile < NT) {
                    int m = main_flags(tile, 6) | (tile >= 6 * TPH ? M_USE1 : 0);
                    if (hc < 16 && hc && nown == 0 && !(np >> 16)) {
                        m |= M_SW;
                        np |= 1 << 16;
                    }
                    meta[pc >> 3] = m;
                    load_tile(tile, false);
                    if (stat) np++;
                    else nxt = nown > 0 ? (int)ticket(1) : -1;
                } else {
                    if ((hc & 15) != 6 || hc < 6 + JCNT * 16) mbar_arrive(sb + OFF_JB);
                    meta[pc >> 3] = M_END | M_SVC | 6 | (0x366 << 16);
                    mbar_arrive(sb + OFF_FULL + (pc & ~7u));
                    mbar_arrive(sb + OFF_JB + 16);
                    break;
                }
                np = (np & ~0xff00) | ((np + 256) & 0xff00);
                hslot[7] = (nown << 8) | (np & 255);
                post();
            }
        }
    }
}

__device__ float f_x[DM], f_q[NQ], f_o[NQ], f_h[FF];
__device__ float f_part[16 * 64 * 258];

__device__ float fb_block_sum(float v, float* sm) {
    for (int o = 16; o > 0; o >>= 1) v += __shfl_xor_sync(0xffffffffu, v, o);
    __syncthreads();
    if ((threadIdx.x & 31) == 0) sm[threadIdx.x >> 5] = v;
    __syncthreads();
    float r = 0.f;
    for (int i = 0; i < 8; i++) r += sm[i];
    return r;
}
__global__ void __launch_bounds__(256) fb_gemv(int mode, int layer, Params P) {
    __shared__ float in[NQ];
    __shared__ float sm[8], red[256];
    const int t = threadIdx.x;
    const int K = mode == 1 ? NQ : (mode == 3 ? FF : DM), N = mode == 0 ? NQ : (mode == 2 ? FF : DM);
    const __nv_bfloat16* W = mode == 0 ? P.wq : (mode == 1 ? P.wo : (mode == 2 ? P.w1 : P.w2));
    const bool x_in = layer == 0 && mode < 2;
    if (mode & 1) {
        for (int k = t; k < K; k += 256) in[k] = mode == 1 ? f_o[k] : f_h[k];
    } else {
        float s = 0.f;
        for (int k = t; k < DM; k += 256) s += in[k] = x_in ? __bfloat162float(P.x[k]) : f_x[k];
        const float m = fb_block_sum(s, sm) / DM;
        float q = 0.f;
        for (int k = t; k < DM; k += 256) q += (in[k] - m) * (in[k] - m);
        const float sd = bfr(sqrtf(bfr(bfr(fb_block_sum(q, sm) / DM) + 1e-5f)));
        for (int k = t; k < DM; k += 256) in[k] = bfr(bfr(in[k] - bfr(m)) / sd);
    }
    __syncthreads();
    const int n = blockIdx.x * 32 + (t & 31);
    float a = 0.f;
    for (int k = t >> 5; k < K; k += 8) a += in[k] * __bfloat162float(W[(size_t)k * N + n]);
    red[t] = a;
    __syncthreads();
    if (t < 32) {
        for (int i = 1; i < 8; i++) a += red[t + 32 * i];
        a = bfr(a);
        if (mode == 0) f_q[n] = a;
        else if (mode == 1) f_x[n] = bfr((x_in ? __bfloat162float(P.x[n]) : f_x[n]) + a);
        else if (mode == 2) f_h[n] = bfr(gelu_tanh(bfr(a + __bfloat162float(P.b1[n]))));
        else {
            const float r = bfr(f_x[n] + bfr(a + __bfloat162float(P.b2[n])));
            f_x[n] = r;
            if (layer) P.out[n] = __float2bfloat16_rn(r);
        }
    }
}
__global__ void __launch_bounds__(256) fb_attn(Params P) {
    __shared__ float sc[2][1024];
    __shared__ float sm[8];
    const int t = threadIdx.x, lane = t & 31, h = blockIdx.y;
    const size_t base = ((size_t)h * 65536 + blockIdx.x * 1024) * 256;
    float q[2][8];
    for (int e = 0; e < 2; e++)
        for (int i = 0; i < 8; i++) q[e][i] = f_q[(2 * h + e) * 256 + lane * 8 + i];
    for (int k = t >> 5; k < 1024; k += 8) {
        const uint4 u = *(const uint4*)(P.k + base + (size_t)k * 256 + lane * 8);
        const float kv[8] = {bf_lo(u.x), bf_hi(u.x), bf_lo(u.y), bf_hi(u.y), bf_lo(u.z), bf_hi(u.z), bf_lo(u.w), bf_hi(u.w)};
        float s0 = 0.f, s1 = 0.f;
        for (int i = 0; i < 8; i++) { s0 += q[0][i] * kv[i]; s1 += q[1][i] * kv[i]; }
        for (int o = 16; o > 0; o >>= 1) { s0 += __shfl_xor_sync(0xffffffffu, s0, o); s1 += __shfl_xor_sync(0xffffffffu, s1, o); }
        if (lane == 0) { sc[0][k] = bfr(s0) * 0.0625f; sc[1][k] = bfr(s1) * 0.0625f; }
    }
    __syncthreads();
    float m[2], l[2];
    for (int e = 0; e < 2; e++) {
        float mx = -INFINITY;
        for (int k = 0; k < 1024; k++) mx = fmaxf(mx, sc[e][k]);
        __syncthreads();
        float s = 0.f;
        for (int k = t; k < 1024; k += 256) s += sc[e][k] = expf(sc[e][k] - mx);
        m[e] = mx;
        l[e] = fb_block_sum(s, sm);
    }
    float o0 = 0.f, o1 = 0.f;
    for (int k = 0; k < 1024; k++) {
        const float v = __bfloat162float(P.v[base + (size_t)k * 256 + t]);
        o0 += sc[0][k] * v;
        o1 += sc[1][k] * v;
    }
    for (int e = 0; e < 2; e++) {
        float* p = f_part + ((2 * h + e) * 64 + blockIdx.x) * 258;
        p[t] = e ? o1 : o0;
        if (t == 0) { p[256] = m[e]; p[257] = l[e]; }
    }
}
__global__ void __launch_bounds__(256) fb_merge() {
    const float* p = f_part + blockIdx.x * 64 * 258;
    float M = -INFINITY, L = 0.f, o = 0.f;
    for (int c = 0; c < 64; c++) M = fmaxf(M, p[c * 258 + 256]);
    for (int c = 0; c < 64; c++) {
        const float w = expf(p[c * 258 + 256] - M);
        L += w * p[c * 258 + 257];
        o += w * p[c * 258 + threadIdx.x];
    }
    f_o[blockIdx.x * 256 + threadIdx.x] = bfr(o / L);
}

typedef CUresult (*EncodeFn)(CUtensorMap*, CUtensorMapDataType, cuuint32_t, void*, const cuuint64_t*, const cuuint64_t*,
                             const cuuint32_t*, const cuuint32_t*, CUtensorMapInterleave, CUtensorMapSwizzle,
                             CUtensorMapL2promotion, CUtensorMapFloatOOBfill);

bool make_kv_map(EncodeFn fn, CUtensorMap* tm, const void* p, int box_bytes) {
    cuuint64_t dims[4] = {64, 8, 4, 65536};
    cuuint64_t str[3] = {512, 128, 4096};
    cuuint32_t box[4] = {64, 8, 4, (cuuint32_t)(box_bytes / 4096)};
    cuuint32_t es[4] = {1, 1, 1, 1};
    return fn(tm, CU_TENSOR_MAP_DATA_TYPE_BFLOAT16, 4, (void*)p, dims, str, box, es, CU_TENSOR_MAP_INTERLEAVE_NONE,
              CU_TENSOR_MAP_SWIZZLE_128B, CU_TENSOR_MAP_L2_PROMOTION_NONE, CU_TENSOR_MAP_FLOAT_OOB_FILL_NONE) == CUDA_SUCCESS;
}
bool make_wq_map(EncodeFn fn, CUtensorMap* tm, const void* p) {
    cuuint64_t dims[2] = {NQ, DM};
    cuuint64_t str[1] = {NQ * 2};
    cuuint32_t box[2] = {32, 224};
    cuuint32_t es[2] = {1, 1};
    return fn(tm, CU_TENSOR_MAP_DATA_TYPE_BFLOAT16, 2, (void*)p, dims, str, box, es, CU_TENSOR_MAP_INTERLEAVE_NONE,
              CU_TENSOR_MAP_SWIZZLE_NONE, CU_TENSOR_MAP_L2_PROMOTION_NONE, CU_TENSOR_MAP_FLOAT_OOB_FILL_NONE) == CUDA_SUCCESS;
}

}

extern "C" void kernel_launch(void* const* d_in, const int* in_sizes, int n_in, void* d_out, int out_size) {
    static EncodeFn enc = nullptr;
    static int grid = -1;
    if (grid < 0) {
        void* fn = nullptr;
        cudaDriverEntryPointQueryResult qr;
        cudaGetDriverEntryPoint("cuTensorMapEncodeTiled", &fn, cudaEnableDefault, &qr);
        enc = (EncodeFn)fn;
        int dev = 0, nsm = 0, occ = 0;
        cudaGetDevice(&dev);
        cudaDeviceGetAttribute(&nsm, cudaDevAttrMultiProcessorCount, dev);
        if (cudaFuncSetAttribute(fused_kernel, cudaFuncAttributeMaxDynamicSharedMemorySize, SMEM_TOTAL) == cudaSuccess)
            cudaOccupancyMaxActiveBlocksPerMultiprocessor(&occ, fused_kernel, 512, SMEM_TOTAL);
        (void)cudaGetLastError();
        grid = (enc && occ >= 1 && nsm >= 128) ? (nsm < MAXG ? nsm : MAXG) : 0;
    }
    Params P;
    P.x = (const __nv_bfloat16*)d_in[0];
    P.k = (const __nv_bfloat16*)d_in[1];
    P.v = (const __nv_bfloat16*)d_in[2];
    P.wq = (const __nv_bfloat16*)d_in[3];
    P.wo = (const __nv_bfloat16*)d_in[4];
    P.w1 = (const __nv_bfloat16*)d_in[6];
    P.b1 = (const __nv_bfloat16*)d_in[7];
    P.w2 = (const __nv_bfloat16*)d_in[8];
    P.b2 = (const __nv_bfloat16*)d_in[9];
    P.out = (__nv_bfloat16*)d_out;
    P.ta0 = OWN0 - grid * NA;
    P.tkeep = NT - grid * (NS + 1);
    P.tk0 = P.tkeep - 792;
    CUtensorMap tmK, tmV, tmKs, tmVs, tmQ;
    if (grid && make_kv_map(enc, &tmK, P.k, 16384) && make_kv_map(enc, &tmV, P.v, 16384) && make_kv_map(enc, &tmKs, P.k, PIECE) &&
        make_kv_map(enc, &tmVs, P.v, PIECE) && make_wq_map(enc, &tmQ, P.wq)) {
        fused_kernel<<<grid, 512, SMEM_TOTAL>>>(tmK, tmV, tmKs, tmVs, tmQ, P);
        return;
    }
    for (int layer = 0; layer < 2; layer++) {
        fb_gemv<<<NQ / 32, 256>>>(0, layer, P);
        fb_attn<<<dim3(64, 8), 256>>>(P);
        fb_merge<<<16, 256>>>();
        fb_gemv<<<DM / 32, 256>>>(1, layer, P);
        fb_gemv<<<FF / 32, 256>>>(2, layer, P);
        fb_gemv<<<DM / 32, 256>>>(3, layer, P);
    }
}
```

```cpp
#include <cuda_runtime.h>
#include <cuda_bf16.h>
#include <cuda.h>
#include <stdint.h>
#include <limits.h>

namespace {

constexpr int DM = 448;
constexpr int FF = 1792;
constexpr int NQ = 4096;
constexpr int TPH = 2048;
constexpr int NT = 8 * TPH;
constexpr int OWN0 = 7 * TPH;
constexpr int NS = 7;
constexpr int NA = 6;
constexpr int DEPTH = 2;
constexpr int DEPTH_MIX = 4;
constexpr int NSTAT = 2;
constexpr int PIECE = 4096;
constexpr int JCNT = 5;
constexpr int PF_DELAY_W = 1000;
constexpr int PF_DELAY_T = 3000;
constexpr int PF_PACE = 1350;
constexpr int REG_H = NA * 32 + 8, REG_C = 88, REG_P = 24;
static_assert(2 * REG_H + REG_C + REG_P <= 512, "register file");
constexpr bool FOLD_Q = false, FOLD_M = true;
constexpr int SLOT = 32768;
constexpr int MAXG = 144;
constexpr int OWNCAP = 32;
constexpr int SPIN_MAX = 1 << 22;

constexpr int M_USE1 = 1 << 8;
constexpr int M_SVC = 1 << 9;
constexpr int M_SIDE = 1 << 10;
constexpr int M_END = 1 << 11;
constexpr int M_NOP = 1 << 12;
constexpr int M_SW = 1 << 13;

constexpr int OFF_SC = NS * SLOT;
constexpr int OFF_RED = OFF_SC + 2048;
constexpr int OFF_FULL = OFF_RED + 512;
constexpr int OFF_EMPTY = OFF_FULL + 64;
constexpr int OFF_HREQ = OFF_EMPTY + 64;
constexpr int OFF_META = OFF_HREQ + 64;
constexpr int OFF_HSLOT = OFF_META + 32;
constexpr int OFF_JB = OFF_HSLOT + 32;
constexpr int OFF_XO = OFF_JB + 32;
constexpr int OFF_OWN = OFF_XO + 128;
constexpr int SMEM_TOTAL = OFF_OWN + OWNCAP * 2;
static_assert(SMEM_TOTAL <= 232448, "smem");
static_assert(NS <= 7 && NA <= 6, "bars");

__device__ __align__(128) uint4 g_rec[3 * 128 * MAXG * 2];
__device__ __align__(128) uint4 g_q[1024];
__device__ __align__(128) uint4 g_ma[14 * 128 * 8];
__device__ __align__(128) uint4 g_mb[128 * 112];
__device__ __align__(128) unsigned g_ctr0[32];
__device__ __align__(128) unsigned g_ctr1[32];
__device__ unsigned g_epoch;

__device__ __forceinline__ uint32_t smem_u32(const void* p) { return (uint32_t)__cvta_generic_to_shared(p); }
__device__ __forceinline__ int tid_now() {
    int t;
    asm volatile("mov.u32 %0, %tid.x;" : "=r"(t));
    return t;
}
__device__ __forceinline__ uint64_t pol_first() {
    uint64_t p;
    asm volatile("createpolicy.fractional.L2::evict_first.b64 %0, 1.0;" : "=l"(p));
    return p;
}
__device__ __forceinline__ uint64_t pol_normal() {
    uint64_t p;
    asm volatile("createpolicy.fractional.L2::evict_normal.b64 %0, 1.0;" : "=l"(p));
    return p;
}
__device__ __forceinline__ void mbar_init(uint32_t bar, int cnt) {
    asm volatile("mbarrier.init.shared.b64 [%0], %1;" ::"r"(bar), "r"(cnt) : "memory");
}
__device__ __forceinline__ void mbar_expect(uint32_t bar, uint32_t bytes) {
    asm volatile("mbarrier.arrive.expect_tx.shared.b64 _, [%0], %1;" ::"r"(bar), "r"(bytes) : "memory");
}
__device__ __forceinline__ void mbar_arrive(uint32_t bar) {
    asm volatile("mbarrier.arrive.shared.b64 _, [%0];" ::"r"(bar) : "memory");
}
__device__ __forceinline__ void mbar_wait(uint32_t bar, uint32_t parity) {
    int it = 0;
    while (true) {
        uint32_t ok;
        asm volatile("{\n.reg .pred p;\nmbarrier.try_wait.parity.shared.b64 p, [%1], %2;\nselp.u32 %0, 1, 0, p;\n}"
                     : "=r"(ok) : "r"(bar), "r"(parity) : "memory");
        if (ok) break;
        if (++it > SPIN_MAX) __trap();
    }
}
__device__ __forceinline__ void tma4(uint32_t dst, const CUtensorMap* tm, int c3, uint32_t bar, uint64_t pol) {
    asm volatile(
        "cp.async.bulk.tensor.4d.shared::cluster.global.mbarrier::complete_tx::bytes.L2::cache_hint "
        "[%0], [%1, {%3,%3,%3,%4}], [%2], %5;" ::"r"(dst), "l"(tm), "r"(bar), "r"(0), "r"(c3), "l"(pol) : "memory");
}
__device__ __forceinline__ void tma2(uint32_t dst, const CUtensorMap* tm, int c0, int c1, uint32_t bar) {
    asm volatile(
        "cp.async.bulk.tensor.2d.shared::cluster.global.mbarrier::complete_tx::bytes "
        "[%0], [%1, {%3,%4}], [%2];" ::"r"(dst), "l"(tm), "r"(bar), "r"(c0), "r"(c1) : "memory");
}
__device__ __forceinline__ void tma4_prefetch_plain(const CUtensorMap* tm, int c3) {
    asm volatile("cp.async.bulk.prefetch.tensor.4d.L2.global [%0, {%1,%1,%1,%2}];" ::"l"(tm), "r"(0), "r"(c3) : "memory");
}
__device__ __forceinline__ uint32_t timer_lo() {
    uint32_t t;
    asm volatile("mov.u32 %0, %globaltimer_lo;" : "=r"(t));
    return t;
}
__device__ __forceinline__ void tma4_prefetch(const CUtensorMap* tm, int c3, uint64_t pol) {
    asm volatile("cp.async.bulk.prefetch.tensor.4d.L2.global.L2::cache_hint [%0, {%1,%1,%1,%2}], %3;" ::"l"(tm), "r"(0), "r"(c3), "l"(pol) : "memory");
}
__device__ __forceinline__ unsigned ticket(int which) {
    unsigned r;
    if (which) asm volatile("atom.relaxed.gpu.global.add.u32 %0, [%1], 1;" : "=r"(r) : "l"(g_ctr1) : "memory");
    else asm volatile("atom.relaxed.gpu.global.add.u32 %0, [%1], 1;" : "=r"(r) : "l"(g_ctr0) : "memory");
    return r;
}
__device__ __forceinline__ void l2_prefetch(const void* src, uint32_t bytes) {
    asm volatile("cp.async.bulk.prefetch.L2.global [%0], %1;" ::"l"(src), "r"(bytes) : "memory");
}
__device__ __forceinline__ void bar_c() { asm volatile("bar.sync 1, 128;" ::: "memory"); }
__device__ __forceinline__ bool bar_c_and(bool v) {
    uint32_t r;
    asm volatile("{\n.reg .pred p, q;\nsetp.ne.u32 q, %1, 0;\nbar.red.and.pred p, 3, 128, q;\nselp.u32 %0, 1, 0, p;\n}"
                 : "=r"(r) : "r"((uint32_t)v) : "memory");
    return r != 0;
}
__device__ __forceinline__ void ldsm4(uint32_t* r, uint32_t a) {
    asm volatile("ldmatrix.sync.aligned.m8n8.x4.shared.b16 {%0,%1,%2,%3}, [%4];"
                 : "=r"(r[0]), "=r"(r[1]), "=r"(r[2]), "=r"(r[3]) : "r"(a) : "memory");
}
__device__ __forceinline__ void ldsm4t(uint32_t* r, uint32_t a) {
    asm volatile("ldmatrix.sync.aligned.m8n8.x4.trans.shared.b16 {%0,%1,%2,%3}, [%4];"
                 : "=r"(r[0]), "=r"(r[1]), "=r"(r[2]), "=r"(r[3]) : "r"(a) : "memory");
}
__device__ __forceinline__ void mma16816(float* c, const uint32_t* a, uint32_t b0, uint32_t b1) {
    asm volatile("mma.sync.aligned.m16n8k16.row.col.f32.bf16.bf16.f32 {%0,%1,%2,%3}, {%4,%5,%6,%7}, {%8,%9}, {%0,%1,%2,%3};"
                 : "+f"(c[0]), "+f"(c[1]), "+f"(c[2]), "+f"(c[3])
                 : "r"(a[0]), "r"(a[1]), "r"(a[2]), "r"(a[3]), "r"(b0), "r"(b1));
}
__device__ __forceinline__ void st_pkt(void* p, uint32_t a, uint32_t b, uint32_t c, uint32_t d) {
    asm volatile("{\n.reg .b128 v;\n.reg .b64 lo, hi;\nmov.b64 lo, {%1,%2};\nmov.b64 hi, {%3,%4};\nmov.b128 v, {lo,hi};\n"
                 "st.relaxed.gpu.global.b128 [%0], v;\n}" ::"l"(p), "r"(a), "r"(b), "r"(c), "r"(d) : "memory");
}
__device__ __forceinline__ uint4 ld_pkt(const void* p) {
    uint4 r;
    asm volatile("{\n.reg .b128 v;\n.reg .b64 lo, hi;\nld.relaxed.gpu.global.b128 v, [%4];\nmov.b128 {lo,hi}, v;\n"
                 "mov.b64 {%0,%1}, lo;\nmov.b64 {%2,%3}, hi;\n}"
                 : "=r"(r.x), "=r"(r.y), "=r"(r.z), "=r"(r.w) : "l"(p) : "memory");
    return r;
}
__device__ __forceinline__ void st_pkt4(void* p, const float* v, uint32_t tag) {
    st_pkt(p, __byte_perm(__float_as_uint(v[0]), tag, 0x3214), __float_as_uint(v[1]), __float_as_uint(v[2]), __float_as_uint(v[3]));
}
__device__ __forceinline__ uint4 ldg128(const void* p, uint64_t pol) {
    uint4 r;
    asm volatile("ld.global.nc.L2::cache_hint.v4.u32 {%0,%1,%2,%3}, [%4], %5;"
                 : "=r"(r.x), "=r"(r.y), "=r"(r.z), "=r"(r.w) : "l"(p), "l"(pol) : "memory");
    return r;
}
__device__ __forceinline__ uint32_t ldg32p(const void* p, uint64_t pol) {
    uint32_t r;
    asm volatile("ld.global.nc.L2::cache_hint.u32 %0, [%1], %2;" : "=r"(r) : "l"(p), "l"(pol) : "memory");
    return r;
}
__device__ __forceinline__ uint2 ldg64p(const void* p, uint64_t pol) {
    uint2 r;
    asm volatile("ld.global.nc.L2::cache_hint.v2.u32 {%0,%1}, [%2], %3;" : "=r"(r.x), "=r"(r.y) : "l"(p), "l"(pol) : "memory");
    return r;
}
__device__ __forceinline__ uint2 ldg64(const void* p) {
    uint2 r;
    asm volatile("ld.global.nc.v2.u32 {%0,%1}, [%2];" : "=r"(r.x), "=r"(r.y) : "l"(p) : "memory");
    return r;
}
__device__ __forceinline__ float bf_lo(uint32_t u) { return __uint_as_float(u << 16); }
__device__ __forceinline__ float bf_hi(uint32_t u) { return __uint_as_float(u & 0xffff0000u); }
__device__ __forceinline__ uint32_t pack_bf(float lo, float hi) {
    uint32_t r;
    asm("cvt.rn.bf16x2.f32 %0, %1, %2;" : "=r"(r) : "f"(hi), "f"(lo));
    return r;
}
__device__ __forceinline__ float rcp(float x) {
    float r;
    asm("rcp.approx.ftz.f32 %0, %1;" : "=f"(r) : "f"(x));
    return r;
}
__device__ __forceinline__ float warp_max(float x) {
    int k = __float_as_int(x);
    k ^= (k >> 31) & 0x7fffffff;
    k = __reduce_max_sync(0xffffffffu, k);
    k ^= (k >> 31) & 0x7fffffff;
    return __int_as_float(k);
}
__device__ __forceinline__ float bfr(float x) { return __uint_as_float(pack_bf(0.f, x)); }
__device__ __forceinline__ float ex2(float x) {
    float r;
    asm("ex2.approx.ftz.f32 %0, %1;" : "=f"(r) : "f"(x));
    return r;
}

struct St {
    float acc[16];
    uint32_t q[8];
    float m0, l0, m1, l1;
};

struct Params {
    const __nv_bfloat16 *x, *k, *v, *wq, *wo, *w1, *b1, *w2, *b2;
    __nv_bfloat16* out;
    int ta0;
    int tk0, tkeep;
};

__device__ __forceinline__ void st_loadq(St& s, int h0, int h1, uint32_t tag) {
    const int tid = tid_now();
    const int lane = tid & 31, w = tid >> 5;
    const int h = lane < 16 ? h0 : h1;
    const uint4* p = g_q + (((2 * h + ((lane >> 2) & 1)) * 4 + w) * 16 + (lane & 3));
    p += lane & 8;
    int it = 0;
    uint4 a, b;
    while (true) {
        a = ld_pkt(p);
        b = ld_pkt(p + 4);
        if (__all_sync(0xffffffffu, a.z == tag && b.z == tag)) break;
        if (++it > SPIN_MAX) __trap();
    }
    const uint32_t o0 = __shfl_xor_sync(0xffffffffu, a.x, 8), o1 = __shfl_xor_sync(0xffffffffu, a.y, 8);
    const uint32_t o2 = __shfl_xor_sync(0xffffffffu, b.x, 8), o3 = __shfl_xor_sync(0xffffffffu, b.y, 8);
    const bool up = lane & 8;
    s.q[0] = up ? o0 : a.x; s.q[1] = up ? o1 : a.y; s.q[2] = up ? o2 : b.x; s.q[3] = up ? o3 : b.y;
    s.q[4] = up ? a.x : o0; s.q[5] = up ? a.y : o1; s.q[6] = up ? b.x : o2; s.q[7] = up ? b.y : o3;
}

__device__ __forceinline__ void st_flush(St& s, int sg, int buf, int cta, uint32_t tag) {
    const int tid = tid_now();
    const int u = tid & 1;
    uint4* p = g_rec + ((buf * 128 + (tid & ~3)) * MAXG + cta) * 2 + u;
    asm volatile("" : "+l"(p));
    float l = sg ? s.l1 : s.l0;
    l += __shfl_xor_sync(0xffffffffu, l, 1);
    l += __shfl_xor_sync(0xffffffffu, l, 2);
    l += __shfl_xor_sync(0xffffffffu, l, 4);
    l += __shfl_xor_sync(0xffffffffu, l, 8);
    const float y = u ? l : (sg ? s.m1 : s.m0);
    const float yo = __shfl_xor_sync(0xffffffffu, y, 16);
    const bool hi = tid & 16;
    const float ml[2] = {hi ? yo : y, hi ? y : yo};
    const bool mine = ((tid >> 1) & 1) == sg;
#pragma unroll
    for (int r = 0; r < 4; r++) {
        const int o = (r & 1) * 2 + (r >> 1);
        asm volatile("{\n.reg .pred p;\n.reg .b128 v;\n.reg .b64 lo, hi;\nsetp.ne.u32 p, %5, 0;\nmov.b64 lo, {%1,%2};\nmov.b64 hi, {%3,%4};\n"
                     "mov.b128 v, {lo,hi};\n@p st.relaxed.gpu.global.b128 [%0], v;\n}" ::"l"(p + r * MAXG * 2),
                     "f"(u ? s.acc[8 + o] : s.acc[o]), "f"(u ? s.acc[12 + o] : s.acc[4 + o]), "f"(ml[r >> 1]), "r"(tag),
                     "r"((uint32_t)mine) : "memory");
    }
#pragma unroll
    for (int i = 0; i < 16; i++) s.acc[i] = mine ? 0.f : s.acc[i];
    if (sg) { s.m1 = -INFINITY; s.l1 = 0.f; }
    else { s.m0 = -INFINITY; s.l0 = 0.f; }
}

__device__ __forceinline__ bool combine(bool block, float* on, int buf, int G, int cta, uint32_t tag, float* red) {
    const int tid = tid_now();
    const int j = cta & 127;
    const uint4* p = g_rec + ((buf * 128 + j) * MAXG + tid) * 2;
    const bool two = tid + 128 < G;
    const uint4* p2 = two ? p + 256 : p;
    float s[5], m1;
    {
        uint4 a, b, c, d;
        int it = 0;
        bool ok;
        while (true) {
            a = ld_pkt(p);
            b = ld_pkt(p + 1);
            c = ld_pkt(p2);
            d = ld_pkt(p2 + 1);
            ok = __all_sync(0xffffffffu, a.w == tag && b.w == tag && c.w == tag && d.w == tag);
            if (ok || !block) break;
            if (++it > SPIN_MAX) __trap();
        }
        if (!block) {
            if (!bar_c_and(ok)) return false;
        }
        const float ma = __uint_as_float(a.z), mb = two ? __uint_as_float(c.z) : -INFINITY;
        m1 = warp_max(fmaxf(ma, mb));
        const float ms = (m1 == -INFINITY) ? 0.f : m1;
        const float f1 = ex2(ma - ms), f2 = ex2(mb - ms);
        s[0] = f1 * __uint_as_float(a.x) + f2 * __uint_as_float(c.x);
        s[1] = f1 * __uint_as_float(a.y) + f2 * __uint_as_float(c.y);
        s[2] = f1 * __uint_as_float(b.x) + f2 * __uint_as_float(d.x);
        s[3] = f1 * __uint_as_float(b.y) + f2 * __uint_as_float(d.y);
        s[4] = f1 * __uint_as_float(b.z) + f2 * __uint_as_float(d.z);
    }
#pragma unroll
    for (int o = 16; o > 0; o >>= 1) {
#pragma unroll
        for (int i = 0; i < 5; i++) s[i] += __shfl_xor_sync(0xffffffffu, s[i], o);
    }
    if ((tid & 31) == 0) {
        *(float4*)(red + (tid >> 5) * 8) = make_float4(s[0], s[1], s[2], s[3]);
        *(float2*)(red + (tid >> 5) * 8 + 4) = make_float2(s[4], m1);
    }
    bar_c();
    float M = -INFINITY;
#pragma unroll
    for (int i = 0; i < 4; i++) M = fmaxf(M, red[i * 8 + 5]);
    float o4[4] = {0.f, 0.f, 0.f, 0.f}, L = 0.f;
#pragma unroll
    for (int i = 0; i < 4; i++) {
        float4 v = *(const float4*)(red + i * 8);
        float2 lm = *(const float2*)(red + i * 8 + 4);
        float f = ex2(lm.y - M);
        o4[0] += f * v.x; o4[1] += f * v.y; o4[2] += f * v.z; o4[3] += f * v.w;
        L += f * lm.x;
    }
    const float inv = rcp(L);
#pragma unroll
    for (int i = 0; i < 4; i++) on[i] = bfr(o4[i] * inv);
    return true;
}

__device__ __forceinline__ float2 ln_partial(uint2 xp, int lane) {
    const float sh = bf_lo(__shfl_sync(0xffffffffu, xp.x, 0));
    const float d0 = bf_lo(xp.x) - sh, d1 = bf_hi(xp.x) - sh, d2 = bf_lo(xp.y) - sh, d3 = bf_hi(xp.y) - sh;
    float s = lane < 28 ? (d0 + d1) + (d2 + d3) : 0.f;
    float q = lane < 28 ? (d0 * d0 + d1 * d1) + (d2 * d2 + d3 * d3) : 0.f;
#pragma unroll
    for (int o = 16; o > 0; o >>= 1) {
        s += __shfl_xor_sync(0xffffffffu, s, o);
        q += __shfl_xor_sync(0xffffffffu, q, o);
    }
    return make_float2(sh + s * (1.f / 112), q - s * s * (1.f / 112));
}
__device__ __forceinline__ void ln_final(const float2* stat, float& mean, float& rsd) {
    const float4 a = *(const float4*)stat, b = *(const float4*)(stat + 2);
    const float m = ((a.x + a.z) + (b.x + b.z)) * 0.25f;
    const float e0 = a.x - m, e1 = a.z - m, e2 = b.x - m, e3 = b.z - m;
    const float m2 = ((a.y + a.w) + (b.y + b.w)) + 112.f * ((e0 * e0 + e1 * e1) + (e2 * e2 + e3 * e3));
    float sd;
    asm("sqrt.approx.ftz.f32 %0, %1;" : "=f"(sd) : "f"(bfr(bfr(fmaxf(m2 * (1.f / DM), 0.f)) + 1e-5f)));
    mean = bfr(m);
    rsd = rcp(bfr(sd));
}
template <int MT, bool FOLD>
__device__ __forceinline__ void ln_gemv(const uint32_t (*af)[MT][4], uint2 xp, float2* part, float2* stat, int tid) {
    const int lane = tid & 31, w = tid >> 5;
    if (!FOLD) {
        const float2 st = ln_partial(xp, lane);
        if (lane == 0) stat[w] = st;
        bar_c();
        float mean, rsd;
        ln_final(stat, mean, rsd);
        xp.x = pack_bf(bfr(bf_lo(xp.x) - mean) * rsd, bfr(bf_hi(xp.x) - mean) * rsd);
        xp.y = pack_bf(bfr(bf_lo(xp.y) - mean) * rsd, bfr(bf_hi(xp.y) - mean) * rsd);
    }
    float c[2][MT][4];
#pragma unroll
    for (int i = 0; i < 2 * MT * 4; i++) (&c[0][0][0])[i] = 0.f;
    const bool ones = FOLD && (lane & 4);
#pragma unroll
    for (int k = 0; k < 7; k++) {
        uint32_t b0 = __shfl_sync(0xffffffffu, xp.x, k * 4 + (lane & 3));
        uint32_t b1 = __shfl_sync(0xffffffffu, xp.y, k * 4 + (lane & 3));
        if (ones) b0 = b1 = 0x3f803f80u;
#pragma unroll
        for (int m = 0; m < MT; m++) mma16816(c[k & 1][m], af[k][m], b0, b1);
    }
    float2 st;
    if (FOLD) st = ln_partial(xp, lane);
    if ((lane & 3) == 0) {
#pragma unroll
        for (int m = 0; m < MT; m++)
            *(float4*)(part + w * (16 * MT) + (lane >> 2) * (2 * MT) + 2 * m) =
                make_float4(c[0][m][0] + c[1][m][0], c[0][m][1] + c[1][m][1], c[0][m][2] + c[1][m][2], c[0][m][3] + c[1][m][3]);
        if (FOLD && lane == 0) stat[w] = st;
    }
    bar_c();
}
template <int MT, bool FOLD>
__device__ __forceinline__ float2 ln_cols(const float2* part, int col, float mean, float rsd) {
    const float4 a = *(const float4*)(part + col), b = *(const float4*)(part + 16 * MT + col);
    const float4 c = *(const float4*)(part + 32 * MT + col), d = *(const float4*)(part + 48 * MT + col);
    if (!FOLD) return make_float2((a.x + b.x) + (c.x + d.x), (a.z + b.z) + (c.z + d.z));
    return make_float2((((a.x + b.x) + (c.x + d.x)) - mean * ((a.y + b.y) + (c.y + d.y))) * rsd,
                       (((a.z + b.z) + (c.z + d.z)) - mean * ((a.w + b.w) + (c.w + d.w))) * rsd);
}
__device__ __forceinline__ uint32_t pk_lo(uint32_t a, uint32_t b) { return __byte_perm(a, b, 0x5410); }
__device__ __forceinline__ uint32_t pk_hi(uint32_t a, uint32_t b) { return __byte_perm(a, b, 0x7632); }

__device__ __forceinline__ void frag16(uint32_t (*a)[4], const uint4* wr) {
#pragma unroll
    for (int m = 0; m < 8; m++) {
        const uint32_t r0 = (&wr[0 + (m >> 2)].x)[m & 3], r1 = (&wr[2 + (m >> 2)].x)[m & 3];
        const uint32_t r2 = (&wr[4 + (m >> 2)].x)[m & 3], r3 = (&wr[6 + (m >> 2)].x)[m & 3];
        a[m][0] = pk_lo(r0, r1);
        a[m][1] = pk_hi(r0, r1);
        a[m][2] = pk_lo(r2, r3);
        a[m][3] = pk_hi(r2, r3);
#pragma unroll
        for (int i = 0; i < 4; i++) asm volatile("" : "+r"(a[m][i]));
    }
}
__device__ __forceinline__ void gemv16(float* acc, const uint32_t (*a)[4], uint32_t b0, uint32_t b1, int lane) {
    float y[8][4];
#pragma unroll
    for (int m = 0; m < 8; m++) {
        y[m][0] = y[m][1] = y[m][2] = y[m][3] = 0.f;
        mma16816(y[m], a[m], b0, b1);
    }
    const bool t1 = lane & 1, t2 = lane & 2;
#pragma unroll
    for (int i = 0; i < 4; i++) {
        const int m = i >> 1, e = (i & 1) * 2;
        acc[i] += t2 ? (t1 ? y[6 + m][e] : y[4 + m][e]) : (t1 ? y[2 + m][e] : y[m][e]);
    }
}

__device__ __forceinline__ uint2 mb_poll(int cta, int tid, uint32_t tag) {
    const uint4* p = g_mb + cta * 112 + (tid >> 5) * 28 + min(tid & 31, 27);
    int it = 0;
    while (true) {
        const uint4 a = ld_pkt(p);
        if (__all_sync(0xffffffffu, a.z == tag)) return make_uint2(a.x, a.y);
        if (++it > SPIN_MAX) __trap();
    }
}

__device__ __forceinline__ float gelu_tanh(float x) {
    const float u = (-2.f * 0.7978845608028654f * 1.4426950408889634f) * (x + 0.044715f * x * x * x);
    return __fdividef(x, 1.f + ex2(fminf(u, 120.f)));
}

template <bool PRE>
__device__ __forceinline__ void tile_step(St& s, bool sg, const uint32_t (*kf)[4], uint32_t (*a)[4], uint32_t va, uint32_t scw,
                                          uint32_t scr, uint32_t lb, uint32_t ebar) {
    const float SC = 0.0625f * 1.4426950408889634f;
    float c[4][4];
#pragma unroll
    for (int i = 0; i < 4; i++) c[i][0] = c[i][1] = c[i][2] = c[i][3] = 0.f;
    if (PRE) {
#pragma unroll
        for (int i = 0; i < 8; i++) mma16816(c[i & 1], kf[i], s.q[i & 6], s.q[(i & 6) + 1]);
    } else {
#pragma unroll
        for (int i = 0; i < 4; i++) mma16816(c[i], kf[i], s.q[i & 6], s.q[(i & 6) + 1]);
#pragma unroll
        for (int i = 0; i < 4; i++) ldsm4t(a[i], va ^ (i * 32));
#pragma unroll
        for (int i = 4; i < 8; i++) mma16816(c[i & 3], kf[i], s.q[i & 6], s.q[(i & 6) + 1]);
#pragma unroll
        for (int i = 4; i < 8; i++) ldsm4t(a[i], (va ^ ((i & 3) * 32)) + 8192);
    }
    const bool mine = ((lb & 2) != 0) == sg;
    {
        const bool t1 = lb & 1;
        float v[4];
#pragma unroll
        for (int i = 0; i < 4; i++) v[i] = PRE ? (t1 ? c[1][i] : c[0][i]) : (t1 ? c[1][i] + c[3][i] : c[0][i] + c[2][i]);
        asm volatile("{\n.reg .pred p;\nsetp.ne.u32 p, %5, 0;\n@p st.shared.f32 [%0], %1;\n@p st.shared.f32 [%0+128], %2;\n"
                     "@p st.shared.f32 [%0+32], %3;\n@p st.shared.f32 [%0+160], %4;\n}" ::"r"(scw),
                     "f"(v[0]), "f"(v[1]), "f"(v[2]), "f"(v[3]), "r"((uint32_t)mine) : "memory");
    }
    bar_c();
    float2 p0, p1, p2, p3;
    asm volatile("ld.shared.v2.f32 {%0,%1}, [%2];" : "=f"(p0.x), "=f"(p0.y) : "r"(scr) : "memory");
    asm volatile("ld.shared.v2.f32 {%0,%1}, [%2+512];" : "=f"(p1.x), "=f"(p1.y) : "r"(scr) : "memory");
    asm volatile("ld.shared.v2.f32 {%0,%1}, [%2+1024];" : "=f"(p2.x), "=f"(p2.y) : "r"(scr) : "memory");
    asm volatile("ld.shared.v2.f32 {%0,%1}, [%2+1536];" : "=f"(p3.x), "=f"(p3.y) : "r"(scr) : "memory");
    if (!PRE && (lb & 64)) mbar_arrive(ebar);
    float m = sg ? s.m1 : s.m0, l = sg ? s.l1 : s.l0;
    const float s0 = bfr((p0.x + p1.x) + (p2.x + p3.x)) * SC;
    const float s1 = bfr((p0.y + p1.y) + (p2.y + p3.y)) * SC;
    float mx = fmaxf(s0, s1);
    if (__any_sync(0xffffffffu, mx > m)) {
        {
            int k = __float_as_int(mx);
            k ^= (k >> 31) & 0x7fffffff;
            const bool hi = lb & 32;
            const int k0 = __reduce_max_sync(0xffffffffu, hi ? INT_MIN : k);
            const int k1 = __reduce_max_sync(0xffffffffu, hi ? k : INT_MIN);
            k = hi ? k1 : k0;
            k ^= (k >> 31) & 0x7fffffff;
            mx = __int_as_float(k);
        }
        const float mn = fmaxf(mx, m);
        const float al = (mn == -INFINITY) ? 1.f : ex2(m - mn);
        float f0 = __shfl_sync(0xffffffffu, al, 0), f1 = __shfl_sync(0xffffffffu, al, 16);
        if (!mine) f0 = f1 = 1.f;
        l *= al;
        m = mn;
        if (sg) s.m1 = m; else s.m0 = m;
#pragma unroll
        for (int i = 0; i < 4; i++) {
            s.acc[4 * i + 0] *= f0; s.acc[4 * i + 1] *= f1;
            s.acc[4 * i + 2] *= f0; s.acc[4 * i + 3] *= f1;
        }
    }
    const uint32_t pk = pack_bf(ex2(s0 - m), ex2(s1 - m));
    uint32_t b[4];
    const bool col = ((lb & 32) != 0) == sg;
#pragma unroll
    for (int i = 0; i < 4; i++) {
        b[i] = __shfl_sync(0xffffffffu, pk, (lb & 31) + 4 * i);
        if (!col) b[i] = 0;
    }
    l += bf_lo(pk) + bf_hi(pk);
    if (sg) s.l1 = l; else s.l0 = l;
#pragma unroll
    for (int i = 0; i < 8; i++) mma16816(s.acc + 4 * (i & 3), a[i], b[(i >> 2) * 2], b[(i >> 2) * 2 + 1]);
}

__global__ void __launch_bounds__(512, 1)
fused_kernel(const __grid_constant__ CUtensorMap tmK, const __grid_constant__ CUtensorMap tmV,
             const __grid_constant__ CUtensorMap tmKs, const __grid_constant__ CUtensorMap tmVs,
             const __grid_constant__ CUtensorMap tmQ, const Params P) {
    extern __shared__ __align__(1024) unsigned char smem[];
    const int tid = threadIdx.x;
    const int cta = blockIdx.x;
    const int G = gridDim.x;
    const uint32_t sb = smem_u32(smem);
    volatile int* meta = (volatile int*)(smem + OFF_META);
    volatile int* hslot = (volatile int*)(smem + OFF_HSLOT);

    const int warp = __shfl_sync(0xffffffffu, tid >> 5, 0);
    if (warp >= 4 && warp < 12) {
        asm volatile("bar.sync 0, 512;" ::: "memory");
        asm volatile("setmaxnreg.inc.sync.aligned.u32 %0;" ::"n"(REG_H));
        const uint32_t so = sb + (tid - 128) * 16;
        uint4 r[NA * 8];
#pragma unroll
        for (int i = 0; i < NA; i++) {
            mbar_wait(sb + OFF_HREQ + i * 8, 0);
            uint32_t hs;
            asm volatile("ld.shared.u32 %0, [%1];" : "=r"(hs) : "r"(sb + OFF_HSLOT + i * 4) : "memory");
            mbar_wait(sb + OFF_FULL + (hs & ~7u), hs & 1);
            const uint32_t d = so + (hs & ~7u) * (SLOT / 8);
#pragma unroll
            for (int k = 0; k < 8; k++) {
                uint4& v = r[i * 8 + k];
                asm volatile("ld.shared.v4.u32 {%0,%1,%2,%3}, [%4];" : "=r"(v.x), "=r"(v.y), "=r"(v.z), "=r"(v.w) : "r"(d + k * 4096) : "memory");
            }
            asm volatile("bar.sync 2, 256;" ::: "memory");
            if (so == sb) mbar_arrive(sb + OFF_EMPTY + (hs & ~7u));
        }
#pragma unroll
        for (int i = 0; i < NA; i++) {
            mbar_wait(sb + OFF_HREQ + i * 8, 1);
            uint32_t hs;
            asm volatile("ld.shared.u32 %0, [%1];" : "=r"(hs) : "r"(sb + OFF_HSLOT + i * 4) : "memory");
            const uint32_t d = so + (hs & ~7u) * (SLOT / 8);
#pragma unroll
            for (int k = 0; k < 8; k++) {
                const uint4 v = r[i * 8 + k];
                asm volatile("st.shared.v4.u32 [%0], {%1,%2,%3,%4};" ::"r"(d + k * 4096), "r"(v.x), "r"(v.y), "r"(v.z), "r"(v.w) : "memory");
            }
            asm volatile("fence.proxy.async.shared::cta;" ::: "memory");
            asm volatile("bar.sync 2, 256;" ::: "memory");
            if (so == sb) mbar_arrive(sb + OFF_FULL + (hs & ~7u));
        }
    } else if (warp < 4) {
        asm volatile("setmaxnreg.dec.sync.aligned.u32 %0;" ::"n"(REG_C));
        float* sc = (float*)(smem + OFF_SC);
        float* red = (float*)(smem + OFF_RED);
        volatile uint2* xown = (volatile uint2*)(smem + OFF_XO);
        uint32_t tagp;
        asm volatile("ld.relaxed.gpu.global.u32 %0, [%1];" : "=r"(tagp) : "l"(&g_epoch) : "memory");
        uint32_t rs = 2;

#pragma unroll 1
        while (true) {
            const bool first = rs & 2;
            if (cta < 128) {
                const int tid = tid_now();
                const int lane = tid & 31, w = tid >> 5;
                uint2 xp = make_uint2(0, 0);
                uint2 wr[28];
                if (first) {
                    xp = ldg64(P.x + (w * 28 + min(lane, 27)) * 4);
                    asm volatile("bar.sync 0, 512;" ::: "memory");
                    mbar_wait(sb + OFF_JB + 24, 0);
                    const unsigned char* p = smem + (NS - 1) * SLOT + (w * 112 + (lane & 3) * 4) * 64 + (lane >> 2) * 8;
#pragma unroll
                    for (int r = 0; r < 28; r++) wr[r] = *(const uint2*)(p + ((r >> 2) * 16 + (r & 3)) * 64);
                } else {
                    const uint64_t pol = pol_first();
                    const __nv_bfloat16* p = P.wq + (size_t)(w * 112 + (lane & 3) * 4) * NQ + ((cta + 64) & 127) * 32 + (lane >> 2) * 4;
#pragma unroll
                    for (int r = 0; r < 28; r++) wr[r] = ldg64p(p + (size_t)((r >> 2) * 16 + (r & 3)) * NQ, pol);
                }
                uint32_t af[7][2][4];
#pragma unroll
                for (int k = 0; k < 7; k++) {
                    af[k][0][0] = pk_lo(wr[4 * k].x, wr[4 * k + 1].x);
                    af[k][0][1] = pk_hi(wr[4 * k].x, wr[4 * k + 1].x);
                    af[k][0][2] = pk_lo(wr[4 * k + 2].x, wr[4 * k + 3].x);
                    af[k][0][3] = pk_hi(wr[4 * k + 2].x, wr[4 * k + 3].x);
                    af[k][1][0] = pk_lo(wr[4 * k].y, wr[4 * k + 1].y);
                    af[k][1][1] = pk_hi(wr[4 * k].y, wr[4 * k + 1].y);
                    af[k][1][2] = pk_lo(wr[4 * k + 2].y, wr[4 * k + 3].y);
                    af[k][1][3] = pk_hi(wr[4 * k + 2].y, wr[4 * k + 3].y);
#pragma unroll
                    for (int i = 0; i < 8; i++) asm volatile("" : "+r"((&af[k][0][0])[i]));
                }
                uint4* pq = g_q + ((cta + 64) & 127) * 8 + (tid & 7);
                asm volatile("" : "+l"(pq));
                if (first) {
                    tagp = (tagp + 1) << 5;
                } else {
                    xp = mb_poll(cta, tid, tagp | 11);
                    tagp |= 16;
                }
                ln_gemv<2, FOLD_Q>(af, xp, (float2*)sc, (float2*)red, tid);
                if (tid < 8) {
                    float mean = 0.f, rsd = 0.f;
                    if (FOLD_Q) ln_final((const float2*)red, mean, rsd);
                    const int c0 = (tid >> 2) * 16 + (tid & 3) * 2;
                    const float2 v0 = ln_cols<2, FOLD_Q>((const float2*)sc, c0, mean, rsd);
                    const float2 v1 = ln_cols<2, FOLD_Q>((const float2*)sc, c0 + 8, mean, rsd);
                    st_pkt(pq, pack_bf(v0.x, v0.y), pack_bf(v1.x, v1.y), tagp | 15, tagp | 15);
                }
                bar_c();
            } else {
                if (first) {
                    asm volatile("bar.sync 0, 512;" ::: "memory");
                    mbar_wait(sb + OFF_JB + 24, 0);
                    bar_c();
                }
                tagp = first ? (tagp + 1) << 5 : tagp | 16;
            }
            rs &= ~2u;

            St st;
#pragma unroll
            for (int i = 0; i < 16; i++) st.acc[i] = 0.f;
            st.m0 = st.m1 = -INFINITY;
            st.l0 = st.l1 = 0.f;
            uint32_t lds_k, lds_v, scw, scr, src;
            {
                const int t = tid_now();
                const int lane = t & 31, w = t >> 5;
                lds_k = sb + w * 1024 + ((lane >> 3) & 1) * 4096 + (lane & 7) * 128 + (((lane >> 4) ^ (lane & 7)) << 4);
                lds_v = sb + 16384 + w * 1024 + (lane >> 4) * 4096 + (lane & 7) * 128 + ((((lane >> 3) & 1) ^ (lane & 7)) << 4);
                scw = sb + OFF_SC + w * 512 + ((lane & 1) * 16 + (lane >> 2)) * 4;
                scr = sb + OFF_SC + lane * 8;
                src = ((lane >> 2) & 1) * 16 + (lane & 3) + (lane >> 4) * 32 + (t == 0 ? 64 : 0);
                asm volatile("" : "+r"(lds_k), "+r"(lds_v), "+r"(scw), "+r"(scr), "+r"(src));
            }
            if (first && (src & 64)) mbar_arrive(sb + OFF_HREQ + 56);
            mbar_wait(sb + OFF_FULL + (rs & ~7u), rs & 1);
            const int mt0 = meta[rs >> 3];
            if (!(mt0 & M_SVC)) {
                const uint32_t tb = (rs & ~7u) * (SLOT / 8);
                uint32_t kf[8][4], vf[8][4];
#pragma unroll
                for (int i = 0; i < 8; i++) ldsm4(kf[i], ((lds_k + tb) ^ ((i >> 1) * 32)) + (i & 1) * 8192);
#pragma unroll
                for (int i = 0; i < 8; i++) ldsm4t(vf[i], ((lds_v + tb) ^ ((i & 3) * 32)) + (i >> 2) * 8192);
                bar_c();
                if (src & 64) mbar_arrive(sb + OFF_EMPTY + (rs & ~7u));
                __syncwarp();
                st_loadq(st, 0, 7, tagp | 15);
                tile_step<true>(st, (mt0 & M_USE1) != 0, kf, vf, 0, scw, scr, src, 0);
                scw ^= 256;
                scr ^= 256;
                rs += 8;
                if ((rs >> 3) == NS) rs = (rs & 1) ^ 1;
            } else {
                st_loadq(st, 0, 7, tagp | 15);
            }
            int bk = 0;

#pragma unroll 1
            while (true) {
                mbar_wait(sb + OFF_FULL + (rs & ~7u), rs & 1);
                int mt = meta[rs >> 3];
                const uint32_t tb = (rs & ~7u) * (SLOT / 8);
                uint32_t kf[8][4];
#pragma unroll
                for (int i = 0; i < 8; i++) ldsm4(kf[i], ((lds_k + tb) ^ ((i >> 1) * 32)) + (i & 1) * 8192);
                mt &= ~(bk >> 2) | ~M_SVC;
                if (mt & M_SVC) {
                    if ((mt & M_END) && (bk & 0x3ff) == (mt >> 16)) break;
                    asm volatile("" : "+r"(tagp));
                    const int pass = (tagp >> 4) & 1;
                    const int head = mt & 15;
                    if (pass && !(bk & 512) && (head >= 6 || (mt & M_SW))) {
                        st_flush(st, 1, 2, cta, tagp | 7);
                        bk |= 512;
                        if (head >= 6) st_loadq(st, bk & 7, 6, tagp | 15);
                    }
                    if (!(mt & (M_SIDE | M_NOP))) {
                        const bool adv = head != (bk & 15) || (mt & M_END);
#pragma unroll 1
                        while (true) {
                            const int cur = bk & 15, ncomb = (bk >> 4) & 15;
                            int ch;
                            if (ncomb == cur && cur < head) {
                                st_flush(st, 0, cur & 1, cta, tagp | cur);
                                bk++;
                                if (cur + 1 == head && !(mt & M_END)) break;
                                continue;
                            }
                            if (pass && !(bk & 256) && ncomb == cur && ((mt & M_END) || (!adv && cur >= 2))) ch = 7;
                            else if (ncomb < cur) ch = ncomb;
                            else break;
                            const bool s7 = pass && ch == 7;
                            float on[4];
                            const bool ok = combine(adv, on, s7 ? 2 : (ch & 1), G, cta, tagp | ch, red + (bk & 1024 ? 32 : 0));
                            if (ok) *(float4*)(red + 96 + ch * 4) = make_float4(on[0], on[1], on[2], on[3]);
                            bk ^= 1024;
                            if (ok) bk += s7 ? 256 : 16;
                            if (!adv) break;
                        }
                        if (adv && !(mt & (M_USE1 | M_END))) st_loadq(st, head, (bk & 512) ? 6 : 7, tagp | 15);
                    }
                    if (mt & (M_NOP | M_END)) {
                        if (mt & M_END) break;
                        bar_c();
                        if (src & 64) mbar_arrive(sb + OFF_EMPTY + (rs & ~7u));
                        rs += 8;
                        if ((rs >> 3) == NS) rs = (rs & 1) ^ 1;
                        continue;
                    }
                    meta[7] = ((bk >> 4) & 15) < (bk & 15) || (pass && !(bk & 256) && (bk & 15) >= 2);
                    bk |= 2048;
                    continue;
                }
                bk &= ~2048;
                const uint32_t ebar = sb + OFF_EMPTY + (rs & ~7u);
                uint32_t vf[8][4];
                tile_step<false>(st, (mt & M_USE1) != 0, kf, vf, lds_v + tb, scw, scr, src, ebar);
                scw ^= 256;
                scr ^= 256;
                rs += 8;
                if ((rs >> 3) == NS) rs = (rs & 1) ^ 1;
            }
            asm volatile("" : "+r"(tagp));
            const int pass = (tagp >> 4) & 1;
            const int tid = tid_now();
            const int lane = tid & 31, w = tid >> 5;
            float xacc[4] = {0.f, 0.f, 0.f, 0.f};
            mbar_wait(sb + OFF_JB + 8, pass);
            st_flush(st, pass, pass ^ 1, cta, tagp | (7 - pass));
            {
                uint4* pm = g_ma + ((tid >> 3) * 128 + cta) * 8 + (tid & 7);
                asm volatile("" : "+l"(pm));
                if (cta < 128) {
                    uint2 wr[32];
                    {
                        const int row0 = ((cta >> 1) & 1) * 256 + (cta >> 5) * 64 + ((cta >> 2) & 7) + (cta & 1) * 8;
                        const __nv_bfloat16* wp = P.wo + (size_t)row0 * DM + (tid < 112 ? tid : 0) * 4;
                        const uint64_t pol = pol_first();
#pragma unroll
                        for (int i = 0; i < 24; i++) wr[i] = ldg64p(wp + ((i >> 2) * 512 + (i & 3) * 16) * DM, pol);
#pragma unroll
                        for (int i = 0; i < 4; i++) wr[24 + i] = ldg64p(wp + ((6 + pass) * 512 + i * 16) * DM, pol);
#pragma unroll
                        for (int i = 0; i < 4; i++) wr[28 + i] = ldg64p(wp + ((7 - pass) * 512 + i * 16) * DM, pol);
                    }
#pragma unroll
                    for (int i = 0; i < 28; i++) {
                        const float o = red[96 + (i < 24 ? i : i + pass * 4)];
                        xacc[0] += o * bf_lo(wr[i].x);
                        xacc[1] += o * bf_hi(wr[i].x);
                        xacc[2] += o * bf_lo(wr[i].y);
                        xacc[3] += o * bf_hi(wr[i].y);
                    }
#pragma unroll
                    for (int i = 0; i < 4; i++) asm volatile("" : "+f"(xacc[i]));
                    float on[4];
                    combine(true, on, pass ^ 1, G, cta, tagp | (7 - pass), red + 64);
#pragma unroll
                    for (int i = 0; i < 4; i++) {
                        xacc[0] += on[i] * bf_lo(wr[28 + i].x);
                        xacc[1] += on[i] * bf_hi(wr[28 + i].x);
                        xacc[2] += on[i] * bf_lo(wr[28 + i].y);
                        xacc[3] += on[i] * bf_hi(wr[28 + i].y);
                    }
                }
                if (tid < 112 && cta < 128) st_pkt4(pm, xacc, tagp | 8);
            }
            if (cta >= 128) bar_c();
            if (tid == 127) {
                mbar_arrive(sb + OFF_EMPTY + (rs & ~7u));
            }
            rs += 8;
            if ((rs >> 3) == NS) rs = (rs & 1) ^ 1;
            __syncwarp();
            const int own = G - 1 - cta;
            if (own < 14) {
#pragma unroll 1
                for (int stage = 0; stage < 2; stage++) {
                    const uint32_t tg = tagp | (8 + 2 * stage);
                    const uint4* p = g_ma + own * 1024 + tid;
                    uint4 a[8];
                    int it = 0;
                    while (true) {
#pragma unroll
                        for (int k = 0; k < 7; k++) a[k] = ld_pkt(p + k * 128);
                        a[7] = ld_pkt(p + (stage ? 0 : 7 * 128));
                        uint32_t bad = 0;
#pragma unroll
                        for (int k = 0; k < 8; k++) bad |= a[k].x ^ tg;
                        if (__all_sync(0xffffffffu, (bad & 255) == 0)) break;
                        if (++it > SPIN_MAX) __trap();
                    }
                    if (stage) a[7] = make_uint4(0, 0, 0, 0);
                    float v[4];
#define SUM8(c) (((__uint_as_float(a[0].c) + __uint_as_float(a[1].c)) + (__uint_as_float(a[2].c) + __uint_as_float(a[3].c))) + \
                 ((__uint_as_float(a[4].c) + __uint_as_float(a[5].c)) + (__uint_as_float(a[6].c) + __uint_as_float(a[7].c))))
                    v[0] = SUM8(x); v[1] = SUM8(y); v[2] = SUM8(z); v[3] = SUM8(w);
#undef SUM8
                    {
                        const bool up = lane & 16;
                        v[0] = (up ? v[2] : v[0]) + __shfl_xor_sync(0xffffffffu, up ? v[0] : v[2], 16);
                        v[1] = (up ? v[3] : v[1]) + __shfl_xor_sync(0xffffffffu, up ? v[1] : v[3], 16);
                    }
                    {
                        const bool up = lane & 8;
                        v[0] = (up ? v[1] : v[0]) + __shfl_xor_sync(0xffffffffu, up ? v[0] : v[1], 8);
                    }
                    float* rb = sc + stage * 128;
                    rb[w * 32 + (lane & 7) * 4 + (lane >> 4) * 2 + ((lane >> 3) & 1)] = v[0];
                    const uint32_t xo0 = xown[tid & 7].x, xo1 = xown[tid & 7].y;
                    const uint32_t b20 = stage ? xown[8 + (tid & 7)].x : 0u, b21 = stage ? xown[8 + (tid & 7)].y : 0u;
                    bar_c();
                    uint2 xn;
                    {
                        const float* rp = rb + (tid & 7) * 4;
                        const float4 r0 = *(const float4*)(rp), r1 = *(const float4*)(rp + 32);
                        const float4 r2 = *(const float4*)(rp + 64), r3 = *(const float4*)(rp + 96);
                        float t0 = bfr((r0.x + r1.x) + (r2.x + r3.x)), t1 = bfr((r0.y + r1.y) + (r2.y + r3.y));
                        float t2 = bfr((r0.z + r1.z) + (r2.z + r3.z)), t3 = bfr((r0.w + r1.w) + (r2.w + r3.w));
                        xn.x = pack_bf(bf_lo(xo0) + bfr(t0 + bf_lo(b20)), bf_hi(xo0) + bfr(t1 + bf_hi(b20)));
                        xn.y = pack_bf(bf_lo(xo1) + bfr(t2 + bf_lo(b21)), bf_hi(xo1) + bfr(t3 + bf_hi(b21)));
                    }
                    if (stage && pass) {
                        if (tid < 8) *(uint2*)(P.out + own * 32 + tid * 4) = xn;
                        break;
                    }
                    uint4* pp = g_mb + (tid >> 3) * 112 + own * 8 + (tid & 7);
#pragma unroll
                    for (int k = 0; k < 7; k++) st_pkt(pp + ((k + 3) % 7) * 16 * 112, xn.x, xn.y, tg | 1, tg | 1);
                    if (stage) st_pkt(pp + 7 * 16 * 112, xn.x, xn.y, tg | 1, tg | 1);
                    if (tid < 8) { xown[tid].x = xn.x; xown[tid].y = xn.y; }
                    if (tid == 0 && own == 0 && !stage) {
                        if (pass) { g_ctr1[0] = 0; g_epoch = tagp >> 5; }
                        else g_ctr0[0] = 0;
                    }
                    bar_c();
                }
            } else if (cta < 112) {
                uint32_t a1[7][1][4], a2[8][4];
                {
                    const uint64_t pol = pol_first();
                    uint32_t w1r[28];
                    uint4 w2r[8];
                    const __nv_bfloat16* p1 = P.w1 + (size_t)(w * 112 + (lane & 3) * 4) * FF + cta * 16 + (lane >> 2) * 2;
#pragma unroll
                    for (int r = 0; r < 28; r++) w1r[r] = ldg32p(p1 + (size_t)((r >> 2) * 16 + (r & 3)) * FF, pol);
                    const __nv_bfloat16* p2 = P.w2 + (size_t)(cta * 16 + (lane & 3) * 4) * DM + w * 112 + min(lane >> 2, 6) * 8;
#pragma unroll
                    for (int r = 0; r < 8; r++) w2r[r] = ldg128(p2 + (r >> 1) * DM + (r & 1) * 56, pol);
#pragma unroll
                    for (int k = 0; k < 7; k++) {
                        a1[k][0][0] = pk_lo(w1r[4 * k], w1r[4 * k + 1]);
                        a1[k][0][1] = pk_hi(w1r[4 * k], w1r[4 * k + 1]);
                        a1[k][0][2] = pk_lo(w1r[4 * k + 2], w1r[4 * k + 3]);
                        a1[k][0][3] = pk_hi(w1r[4 * k + 2], w1r[4 * k + 3]);
#pragma unroll
                        for (int i = 0; i < 4; i++) asm volatile("" : "+r"(a1[k][0][i]));
                    }
                    frag16(a2, w2r);
                }
                const int pk = w * 28 + (lane >> 2) * 2 + (lane & 1) + (lane & 2) * 7;
                uint4* pm = g_ma + ((pk >> 3) * 128 + cta) * 8 + (pk & 7);
                asm volatile("" : "+l"(pm));
                const uint2 xp = mb_poll(cta, tid, tagp | 9);
                ln_gemv<1, FOLD_M>(a1, xp, (float2*)sc, (float2*)red, tid);
                float mean = 0.f, rsd = 0.f;
                if (FOLD_M) ln_final((const float2*)red, mean, rsd);
                const float2 h0 = ln_cols<1, FOLD_M>((const float2*)sc, (lane & 3) * 4, mean, rsd);
                const float2 h1 = ln_cols<1, FOLD_M>((const float2*)sc, (lane & 3) * 4 + 2, mean, rsd);
                const uint2 bb = *(const uint2*)(smem + OFF_XO + (lane & 3) * 8);
                const uint32_t g0 = pack_bf(gelu_tanh(bfr(bfr(h0.x) + bf_lo(bb.x))), gelu_tanh(bfr(bfr(h0.y) + bf_hi(bb.x))));
                const uint32_t g1 = pack_bf(gelu_tanh(bfr(bfr(h1.x) + bf_lo(bb.y))), gelu_tanh(bfr(bfr(h1.y) + bf_hi(bb.y))));
                xacc[0] = xacc[1] = xacc[2] = xacc[3] = 0.f;
                gemv16(xacc, a2, g0, g1, lane);
                if (lane < 28) st_pkt4(pm, xacc, tagp | 10);
                bar_c();
            }
            if (tagp & 16) break;
        }
    } else {
        asm volatile("setmaxnreg.dec.sync.aligned.u32 %0;" ::"n"(REG_P));
        if (tid == 384) {
            if (sb & 1023) __trap();
#pragma unroll
            for (int i = 0; i < NS; i++) mbar_init(sb + OFF_FULL + i * 8, 1);
            mbar_init(sb + OFF_JB + 24, 1);
            asm volatile("fence.proxy.async.shared::cta;" ::: "memory");
            mbar_expect(sb + OFF_JB + 24, DM * 64);
            tma2(sb + (NS - 1) * SLOT, &tmQ, ((cta + 64) & 127) * 32, 0, sb + OFF_JB + 24);
            tma2(sb + (NS - 1) * SLOT + 224 * 64, &tmQ, ((cta + 64) & 127) * 32, 224, sb + OFF_JB + 24);
#pragma unroll
            for (int i = 0; i < NSTAT; i++) {
                mbar_expect(sb + OFF_FULL + i * 8, SLOT);
                tma4(sb + i * SLOT, &tmK, (cta + i * G) * 4, sb + OFF_FULL + i * 8, pol_first());
                tma4(sb + i * SLOT + 16384, &tmV, (cta + i * G) * 4, sb + OFF_FULL + i * 8, pol_first());
            }
#pragma unroll
            for (int i = 0; i < NS; i++) {
                mbar_init(sb + OFF_EMPTY + i * 8, 2);
                meta[i] = 0;
            }
            meta[7] = 0;
#pragma unroll
            for (int i = 0; i < 8; i++) mbar_init(sb + OFF_HREQ + i * 8, 1);
#pragma unroll
            for (int i = 0; i < 3; i++) mbar_init(sb + OFF_JB + i * 8, 1);
        }
        __syncwarp();
        if (warp == 12) asm volatile("bar.arrive 0, 512;" ::: "memory");
        else asm volatile("bar.sync 0, 512;" ::: "memory");
        if (warp == 13) {
            const int lane = tid - 416;
            if (lane < 16) {
                const int own = G - 1 - cta;
                const __nv_bfloat16* p = own < 14 ? (lane < 8 ? P.x : P.b2) + own * 32 + (lane & 7) * 4
                                                  : P.b1 + (cta < 112 ? cta : 0) * 16 + (lane & 3) * 4;
                *(uint2*)(smem + OFF_XO + lane * 8) = ldg64(p);
            }
#pragma unroll 1
            for (int pass = 0; pass < 2; pass++) {
                mbar_wait(sb + OFF_JB, pass);
                int cta;
                asm volatile("mov.u32 %0, %ctaid.x;" : "=r"(cta));
                if (G - 1 - cta < 14) {
#pragma unroll 1
                    for (int i = lane; i < 1024; i += 32) st_pkt(g_ma + (G - 1 - cta) * 1024 + i, 0, 0, 0, 0);
                }
                if (cta < 128) {
#pragma unroll 1
                    for (int i = lane; i < 112; i += 32) st_pkt(g_mb + cta * 112 + i, 0, 0, 0, 0);
                }
                __threadfence();
                __syncwarp();
                if (lane == 0) mbar_arrive(sb + OFF_JB + 8);
                {
                    const int row = ((cta >> 1) & 1) * 256 + ((cta >> 5) & 3) * 64 + ((cta >> 2) & 7) + (cta & 1) * 8 + (lane >> 2) * 512 + (lane & 3) * 16;
                    const char* wp = (const char*)(P.wo + (size_t)row * DM);
                    mbar_wait(sb + OFF_JB + 16, pass);
                    if (cta < 128) l2_prefetch(wp, DM * 2);
                }
                __syncwarp();
                if (lane == 0) {
                    asm volatile("mov.u32 %0, %ctaid.x;" : "=r"(cta));
                    if (cta < 128) {
                        {
                            const uint32_t t = timer_lo() + PF_DELAY_W;
                            while ((int)(timer_lo() - t) < 0) {}
                        }
                        l2_prefetch((const char*)P.w1 + cta * (DM * FF * 2 / 128), DM * FF * 2 / 128);
                        l2_prefetch((const char*)P.w2 + cta * (DM * FF * 2 / 128), DM * FF * 2 / 128);
                        if (!pass) l2_prefetch((const char*)P.wq + cta * (DM * NQ * 2 / 128), DM * NQ * 2 / 128);
                    }
                    if (!pass) {
                        volatile unsigned short* own = (volatile unsigned short*)(smem + OFF_OWN);
                        uint32_t t = timer_lo() + PF_DELAY_T + (cta & 7) * (PF_PACE / 8);
                        int i = 255, k = 0;
#pragma unroll 1
                        while (true) {
                            while ((int)(timer_lo() - t) < 0) {}
                            const int pr = hslot[7];
                            i = min(i, pr >> 8);
                            k = max(k, pr & 255);
                            int tile;
                            if (i > 0 && own[i - 1] >= P.tkeep) tile = own[--i];
                            else if (k < 1) tile = cta + (k++) * G;
                            else break;
                            tma4_prefetch_plain(&tmK, tile * 4);
                            tma4_prefetch_plain(&tmV, tile * 4);
                            t += PF_PACE;
                        }
                    }
                }
                __syncwarp();
            }
        } else if (tid == 384) {
            volatile unsigned short* own = (volatile unsigned short*)(smem + OFF_OWN);
            const int TA0 = P.ta0;
            uint32_t pc = 0, wc = 0, lc = 0;
            int cn = 0;
            auto adv = [&](uint32_t& c) {
                c += 8;
                if ((c >> 3) == NS) c = (c & 1) ^ 1;
            };
            auto acquire = [&](int depth) {
                while ((cn >> 8) >= depth) {
                    mbar_wait(sb + OFF_FULL + (lc & ~7u), lc & 1);
                    adv(lc);
                    cn -= 256;
                }
                if ((cn & 255) == NS) {
                    mbar_wait(sb + OFF_EMPTY + (wc & ~7u), wc & 1);
                    adv(wc);
                    cn--;
                }
            };
            auto post = [&]() {
                adv(pc);
                cn += 257;
            };
            auto load_tile = [&](int tile, bool keep) {
                const uint32_t bar = sb + OFF_FULL + (pc & ~7u);
                const uint32_t dst = sb + (pc & ~7u) * (SLOT / 8);
                mbar_expect(bar, SLOT);
                if (!keep) {
                    tma4(dst, &tmK, tile * 4, bar, pol_first());
                    tma4(dst + 16384, &tmV, tile * 4, bar, pol_first());
                } else {
#pragma unroll
                    for (int o = 0; o < 16384; o += PIECE) {
                        tma4(dst + o, &tmKs, tile * 4 + (o >> 12), bar, pol_first());
                        tma4_prefetch(&tmKs, tile * 4 + (o >> 12), pol_normal());
                    }
#pragma unroll
                    for (int o = 0; o < 16384; o += PIECE) {
                        tma4(dst + 16384 + o, &tmVs, tile * 4 + (o >> 12), bar, pol_first());
                        tma4_prefetch(&tmVs, tile * 4 + (o >> 12), pol_normal());
                    }
                }
            };
            auto mark = [&](int m) {
                meta[pc >> 3] = m;
                mbar_arrive(sb + OFF_EMPTY + (pc & ~7u));
                mbar_arrive(sb + OFF_FULL + (pc & ~7u));
                post();
            };
            int hc = 0;
            auto main_flags = [&](int tile, int last) {
                const int head = tile >> 11;
                int m = head;
                if (head != (hc & 15)) { hc = head; m |= M_SVC; }
                else {
                    hc += 16;
                    if (hc == last + JCNT * 16) mbar_arrive(sb + OFF_JB);
                    if ((((hc >> 4) + cta) & 3) == 3 && hc >= 2 * 16 && meta[7]) m |= M_SVC;
                }
                return m;
            };
            int nxt = (int)ticket(0);
#pragma unroll 1
            for (int i = 0; i < NSTAT; i++) {
                mbar_arrive(sb + OFF_EMPTY + (pc & ~7u));
                post();
            }
            int na = 0, nown = 0;
#pragma unroll 1
            while (true) {
                acquire(DEPTH);
                if (nxt < 0) nxt = nown < OWNCAP ? (int)ticket(0) : NT;
                if (pc == (NS - 1) * 8) mbar_wait(sb + OFF_HREQ + 56, 0);
                int tile = nxt + NSTAT * G;
                bool isa = false;
                if (tile >= TA0) {
                    isa = na < NA;
                    tile = isa ? TA0 + na * G + cta : tile + G * NA;
                }
                if (tile >= NT) break;
                meta[pc >> 3] = main_flags(tile, 7);
                if (isa) {
                    hslot[na] = pc;
                    mbar_arrive(sb + OFF_HREQ + na * 8);
                    na++;
                    load_tile(tile, false);
                } else {
                    mbar_arrive(sb + OFF_EMPTY + (pc & ~7u));
                    if (tile >= OWN0) own[nown++] = (unsigned short)tile;
                    load_tile(tile, tile >= P.tk0 && tile < P.tkeep);
                    nxt = -1;
                }
                post();
            }
            if ((hc & 15) != 7 || hc < 7 + JCNT * 16) mbar_arrive(sb + OFF_JB);
            mark(M_END | M_SVC | 7 | (0x77 << 16));
            nxt = (int)ticket(1);
            hslot[7] = (nown > NS ? nown - NS : 0) << 8;
            mbar_arrive(sb + OFF_JB + 16);
#pragma unroll 1
            for (int j = 0; j < NS; j++) {
                acquire(NS);
                const int back = j < NS - 1 ? NS - 1 - j : NS;
                mark(nown >= back ? (M_SIDE | M_USE1 | 7) : (M_NOP | M_SVC));
            }
            nown = nown > NS ? nown - NS : 0;
            na = 0;
            hc = 0;
            int np = 0;
#pragma unroll 1
            while (true) {
                const bool side_left = nown > 0 || na < NA;
                acquire(nown > 0 ? DEPTH_MIX : (side_left ? DEPTH + 1 : DEPTH));
                const bool stat = (np & 255) < NSTAT;
                bool side = side_left && !stat &&
                            (nown > 0 ? ((((np >> 8) + cta) & 1) == 0) : ((np >> 16) && (np & 256)));
                int tile = 0;
                if (!side) {
                    if (nxt < 0) nxt = (int)ticket(1);
                    tile = stat ? cta + (np & 255) * G : nxt + NSTAT * G;
                    if (tile >= TA0) tile = NT;
                    side = side_left && tile >= (nown > 0 ? 6 * TPH : NT);
                }
                mbar_arrive(sb + OFF_EMPTY + (pc & ~7u));
                if (side) {
                    if (nown > 0) {
                        meta[pc >> 3] = M_SIDE | M_USE1 | 7;
                        tile = own[--nown];
                        load_tile(tile, false);
                    } else {
                        meta[pc >> 3] = M_SIDE | M_USE1 | 6 | ((na | (np >> 16)) ? 0 : M_SVC);
                        hslot[na] = pc;
                        mbar_arrive(sb + OFF_HREQ + na * 8);
                        na++;
                    }
                } else if (tile < NT) {
                    int m = main_flags(tile, 6) | (tile >= 6 * TPH ? M_USE1 : 0);
                    if (hc < 16 && hc && nown == 0 && !(np >> 16)) {
                        m |= M_SW;
                        np |= 1 << 16;
                    }
                    meta[pc >> 3] = m;
                    load_tile(tile, false);
                    if (stat) np++;
                    else nxt = nown > 0 ? (int)ticket(1) : -1;
                } else {
                    if ((hc & 15) != 6 || hc < 6 + JCNT * 16) mbar_arrive(sb + OFF_JB);
                    meta[pc >> 3] = M_END | M_SVC | 6 | (0x366 << 16);
                    mbar_arrive(sb + OFF_FULL + (pc & ~7u));
                    mbar_arrive(sb + OFF_JB + 16);
                    break;
                }
                np = (np & ~0xff00) | ((np + 256) & 0xff00);
                hslot[7] = (nown << 8) | (np & 255);
                post();
            }
        }
    }
}

__device__ float f_x[DM], f_q[NQ], f_o[NQ], f_h[FF];
__device__ float f_part[16 * 64 * 258];

__device__ float fb_block_sum(float v, float* sm) {
    for (int o = 16; o > 0; o >>= 1) v += __shfl_xor_sync(0xffffffffu, v, o);
    __syncthreads();
    if ((threadIdx.x & 31) == 0) sm[threadIdx.x >> 5] = v;
    __syncthreads();
    float r = 0.f;
    for (int i = 0; i < 8; i++) r += sm[i];
    return r;
}
__global__ void __launch_bounds__(256) fb_gemv(int mode, int layer, Params P) {
    __shared__ float in[NQ];
    __shared__ float sm[8], red[256];
    const int t = threadIdx.x;
    const int K = mode == 1 ? NQ : (mode == 3 ? FF : DM), N = mode == 0 ? NQ : (mode == 2 ? FF : DM);
    const __nv_bfloat16* W = mode == 0 ? P.wq : (mode == 1 ? P.wo : (mode == 2 ? P.w1 : P.w2));
    const bool x_in = layer == 0 && mode < 2;
    if (mode & 1) {
        for (int k = t; k < K; k += 256) in[k] = mode == 1 ? f_o[k] : f_h[k];
    } else {
        float s = 0.f;
        for (int k = t; k < DM; k += 256) s += in[k] = x_in ? __bfloat162float(P.x[k]) : f_x[k];
        const float m = fb_block_sum(s, sm) / DM;
        float q = 0.f;
        for (int k = t; k < DM; k += 256) q += (in[k] - m) * (in[k] - m);
        const float sd = bfr(sqrtf(bfr(bfr(fb_block_sum(q, sm) / DM) + 1e-5f)));
        for (int k = t; k < DM; k += 256) in[k] = bfr(bfr(in[k] - bfr(m)) / sd);
    }
    __syncthreads();
    const int n = blockIdx.x * 32 + (t & 31);
    float a = 0.f;
    for (int k = t >> 5; k < K; k += 8) a += in[k] * __bfloat162float(W[(size_t)k * N + n]);
    red[t] = a;
    __syncthreads();
    if (t < 32) {
        for (int i = 1; i < 8; i++) a += red[t + 32 * i];
        a = bfr(a);
        if (mode == 0) f_q[n] = a;
        else if (mode == 1) f_x[n] = bfr((x_in ? __bfloat162float(P.x[n]) : f_x[n]) + a);
        else if (mode == 2) f_h[n] = bfr(gelu_tanh(bfr(a + __bfloat162float(P.b1[n]))));
        else {
            const float r = bfr(f_x[n] + bfr(a + __bfloat162float(P.b2[n])));
            f_x[n] = r;
            if (layer) P.out[n] = __float2bfloat16_rn(r);
        }
    }
}
__global__ void __launch_bounds__(256) fb_attn(Params P) {
    __shared__ float sc[2][1024];
    __shared__ float sm[8];
    const int t = threadIdx.x, lane = t & 31, h = blockIdx.y;
    const size_t base = ((size_t)h * 65536 + blockIdx.x * 1024) * 256;
    float q[2][8];
    for (int e = 0; e < 2; e++)
        for (int i = 0; i < 8; i++) q[e][i] = f_q[(2 * h + e) * 256 + lane * 8 + i];
    for (int k = t >> 5; k < 1024; k += 8) {
        const uint4 u = *(const uint4*)(P.k + base + (size_t)k * 256 + lane * 8);
        const float kv[8] = {bf_lo(u.x), bf_hi(u.x), bf_lo(u.y), bf_hi(u.y), bf_lo(u.z), bf_hi(u.z), bf_lo(u.w), bf_hi(u.w)};
        float s0 = 0.f, s1 = 0.f;
        for (int i = 0; i < 8; i++) { s0 += q[0][i] * kv[i]; s1 += q[1][i] * kv[i]; }
        for (int o = 16; o > 0; o >>= 1) { s0 += __shfl_xor_sync(0xffffffffu, s0, o); s1 += __shfl_xor_sync(0xffffffffu, s1, o); }
        if (lane == 0) { sc[0][k] = bfr(s0) * 0.0625f; sc[1][k] = bfr(s1) * 0.0625f; }
    }
    __syncthreads();
    float m[2], l[2];
    for (int e = 0; e < 2; e++) {
        float mx = -INFINITY;
        for (int k = 0; k < 1024; k++) mx = fmaxf(mx, sc[e][k]);
        __syncthreads();
        float s = 0.f;
        for (int k = t; k < 1024; k += 256) s += sc[e][k] = expf(sc[e][k] - mx);
        m[e] = mx;
        l[e] = fb_block_sum(s, sm);
    }
    float o0 = 0.f, o1 = 0.f;
    for (int k = 0; k < 1024; k++) {
        const float v = __bfloat162float(P.v[base + (size_t)k * 256 + t]);
        o0 += sc[0][k] * v;
        o1 += sc[1][k] * v;
    }
    for (int e = 0; e < 2; e++) {
        float* p = f_part + ((2 * h + e) * 64 + blockIdx.x) * 258;
        p[t] = e ? o1 : o0;
        if (t == 0) { p[256] = m[e]; p[257] = l[e]; }
    }
}
__global__ void __launch_bounds__(256) fb_merge() {
    const float* p = f_part + blockIdx.x * 64 * 258;
    float M = -INFINITY, L = 0.f, o = 0.f;
    for (int c = 0; c < 64; c++) M = fmaxf(M, p[c * 258 + 256]);
    for (int c = 0; c < 64; c++) {
        const float w = expf(p[c * 258 + 256] - M);
        L += w * p[c * 258 + 257];
        o += w * p[c * 258 + threadIdx.x];
    }
    f_o[blockIdx.x * 256 + threadIdx.x] = bfr(o / L);
}

typedef CUresult (*EncodeFn)(CUtensorMap*, CUtensorMapDataType, cuuint32_t, void*, const cuuint64_t*, const cuuint64_t*,
                             const cuuint32_t*, const cuuint32_t*, CUtensorMapInterleave, CUtensorMapSwizzle,
                             CUtensorMapL2promotion, CUtensorMapFloatOOBfill);

bool make_kv_map(EncodeFn fn, CUtensorMap* tm, const void* p, int box_bytes) {
    cuuint64_t dims[4] = {64, 8, 4, 65536};
    cuuint64_t str[3] = {512, 128, 4096};
    cuuint32_t box[4] = {64, 8, 4, (cuuint32_t)(box_bytes / 4096)};
    cuuint32_t es[4] = {1, 1, 1, 1};
    return fn(tm, CU_TENSOR_MAP_DATA_TYPE_BFLOAT16, 4, (void*)p, dims, str, box, es, CU_TENSOR_MAP_INTERLEAVE_NONE,
              CU_TENSOR_MAP_SWIZZLE_128B, CU_TENSOR_MAP_L2_PROMOTION_NONE, CU_TENSOR_MAP_FLOAT_OOB_FILL_NONE) == CUDA_SUCCESS;
}
bool make_wq_map(EncodeFn fn, CUtensorMap* tm, const void* p) {
    cuuint64_t dims[2] = {NQ, DM};
    cuuint64_t str[1] = {NQ * 2};
    cuuint32_t box[2] = {32, 224};
    cuuint32_t es[2] = {1, 1};
    return fn(tm, CU_TENSOR_MAP_DATA_TYPE_BFLOAT16, 2, (void*)p, dims, str, box, es, CU_TENSOR_MAP_INTERLEAVE_NONE,
              CU_TENSOR_MAP_SWIZZLE_NONE, CU_TENSOR_MAP_L2_PROMOTION_NONE, CU_TENSOR_MAP_FLOAT_OOB_FILL_NONE) == CUDA_SUCCESS;
}

}

extern "C" void kernel_launch(void* const* d_in, const int* in_sizes, int n_in, void* d_out, int out_size) {
    static EncodeFn enc = nullptr;
    static int grid = -1;
    if (grid < 0) {
        void* fn = nullptr;
        cudaDriverEntryPointQueryResult qr;
        cudaGetDriverEntryPoint("cuTensorMapEncodeTiled", &fn, cudaEnableDefault, &qr);
        enc = (EncodeFn)fn;
        int dev = 0, nsm = 0, occ = 0;
        cudaGetDevice(&dev);
        cudaDeviceGetAttribute(&nsm, cudaDevAttrMultiProcessorCount, dev);
        if (cudaFuncSetAttribute(fused_kernel, cudaFuncAttributeMaxDynamicSharedMemorySize, SMEM_TOTAL) == cudaSuccess)
            cudaOccupancyMaxActiveBlocksPerMultiprocessor(&occ, fused_kernel, 512, SMEM_TOTAL);
        (void)cudaGetLastError();
        grid = (enc && occ >= 1 && nsm >= 128) ? (nsm < MAXG ? nsm : MAXG) : 0;
    }
    Params P;
    P.x = (const __nv_bfloat16*)d_in[0];
    P.k = (const __nv_bfloat16*)d_in[1];
    P.v = (const __nv_bfloat16*)d_in[2];
    P.wq = (const __nv_bfloat16*)d_in[3];
    P.wo = (const __nv_bfloat16*)d_in[4];
    P.w1 = (const __nv_bfloat16*)d_in[6];
    P.b1 = (const __nv_bfloat16*)d_in[7];
    P.w2 = (const __nv_bfloat16*)d_in[8];
    P.b2 = (const __nv_bfloat16*)d_in[9];
    P.out = (__nv_bfloat16*)d_out;
    P.ta0 = OWN0 - grid * NA;
    P.tkeep = NT - grid * (NS + 1);
    P.tk0 = P.tkeep - 792;
    CUtensorMap tmK, tmV, tmKs, tmVs, tmQ;
    if (grid && make_kv_map(enc, &tmK, P.k, 16384) && make_kv_map(enc, &tmV, P.v, 16384) && make_kv_map(enc, &tmKs, P.k, PIECE) &&
        make_kv_map(enc, &tmVs, P.v, PIECE) && make_wq_map(enc, &tmQ, P.wq)) {
        fused_kernel<<<grid, 512, SMEM_TOTAL>>>(tmK, tmV, tmKs, tmVs, tmQ, P);
        return;
    }
    for (int layer = 0; layer < 2; layer++) {
        fb_gemv<<<NQ / 32, 256>>>(0, layer, P);
        fb_attn<<<dim3(64, 8), 256>>>(P);
        fb_merge<<<16, 256>>>();
        fb_gemv<<<DM / 32, 256>>>(1, layer, P);
        fb_gemv<<<FF / 32, 256>>>(2, layer, P);
        fb_gemv<<<DM / 32, 256>>>(3, layer, P);
    }
}
```
